```python
import torch

def _softmax(x, axis=-1):
    return torch.softmax(x, dim=axis)

def _gelu(x):
    return torch.nn.functional.gelu(x, approximate='tanh')

def _silu(x):
    return torch.nn.functional.silu(x)

def _sigmoid(x):
    return torch.sigmoid(x)

def _layernorm(x, axis=-1, eps=1e-05):
    m = x.mean(dim=axis, keepdim=True)
    v = x.var(dim=axis, keepdim=True, unbiased=False)
    return (x - m) / torch.sqrt(v + eps)

def _scatter_add(tgt, idx, src, axis=0):
    return tgt.clone().index_add_(axis, idx, src)

def _segment_sum(src, seg, n):
    out = torch.zeros((n,) + src.shape[1:], dtype=src.dtype)
    return out.index_add_(0, seg, src)

def _pad(x, pw):
    flat = tuple((v for pair in reversed(pw) for v in pair))
    return torch.nn.functional.pad(x, flat)
kernel_name = 'standalone__tensor_product_equiv_mace__graph'

def setup_inputs():

    _w = lambda a: (lambda t: t.to(torch.bfloat16) if t.is_floating_point() else t)(torch.as_tensor(a))
    N, deg = (10000, 16)
    Lmax, C, De = (1, 256, 16)
    M = (Lmax + 1) ** 2
    E = N * deg
    src = (lambda lo, hi, *s: torch.randint(lo, hi, s))(0, N, E).to(torch.int64)
    dst = (lambda lo, hi, *s: torch.randint(lo, hi, s))(0, N, E).to(torch.int64)
    r = (lambda *s: torch.randn(*s, dtype=torch.bfloat16) * 0.05)(E, 3).to(float)
    r = r / (torch.linalg.norm(r, dim=-1, keepdim=True).to(float) + 1e-06)
    rx, ry, rz = (r[:, 0].clone(), r[:, 1].clone(), r[:, 2].clone())
    x2, y2, z2 = (rx * rx, ry * ry, rz * rz)
    sh_list = [torch.ones_like(rx), rx, ry, rz, rx * ry, ry * rz, 2.0 * z2 - x2 - y2, rx * rz, x2 - y2, ry * (3.0 * x2 - y2), rx * ry * rz, ry * (4.0 * z2 - x2 - y2), rz * (2.0 * z2 - 3.0 * x2 - 3.0 * y2), rx * (4.0 * z2 - x2 - y2), rz * (x2 - y2), rx * (x2 - 3.0 * y2)]
    sh16 = torch.stack(sh_list, dim=-1).to(float)
    pad = max(0, M - 16)
    sh_full = torch.cat([sh16, torch.zeros((E, pad), dtype=float)], dim=-1)[:, :M]
    cg = ((lambda *s: torch.randn(*s, dtype=torch.bfloat16) * 0.05)(M, M, M) * (1.0 / float(M))).to(float)
    return {'x': _w(((lambda *s: torch.randn(*s, dtype=torch.bfloat16) * 0.05)(N, M, C) * 0.3).to(float)), 'src': _w(src), 'dst': _w(dst), 'sh': _w(sh_full.to(float)), 'edge_attr': _w(((lambda *s: torch.randn(*s, dtype=torch.bfloat16) * 0.05)(E, De) * 0.3).to(float)), 'cg': _w(cg), 'w_r': _w(((lambda *s: torch.randn(*s, dtype=torch.bfloat16) * 0.05)(De, C) * (1.0 / float(De) ** 0.5)).to(float)), 'w_out': _w(((lambda *s: torch.randn(*s, dtype=torch.bfloat16) * 0.05)(C, C) * (1.0 / float(C) ** 0.5)).to(float))}

def reference(x, src, dst, sh, edge_attr, cg, w_r, w_out):
    N = x.shape[0]
    M = x.shape[1]
    C = x.shape[2]
    h = x[src]
    tp = torch.einsum('uvw,euc,ev->ewc', cg, h, sh)
    rw = edge_attr @ w_r
    msg = tp * rw[:, None, :]
    msg2 = msg.reshape(-1, M * C)
    agg = _segment_sum(msg2, dst, N).reshape(N, M, C)
    out = torch.einsum('nmc,cd->nmd', agg, w_out)
    return out
```

```cpp
#include <cuda_runtime.h>
#include <cuda_bf16.h>
#include <cuda.h>
#include <stdint.h>

#define NS 8
#define PACE 44000
#define T0DELTA 2200
#define GRP 4
#define PFLEAD 1000

#define NCTA 132
#define NPC 76
#define EPC 1216
#define NCH 10
#define CAP 1376
#define CAPP 1504
#define NCONS 13
#define RSTR 544

#define SM_X 0
#define SM_R (NS * 16384)
#define SM_DESC (SM_R + NS * 8 * RSTR)
#define SM_EID (SM_DESC + CAPP * 4)
#define SM_SRC (SM_EID + CAPP * 4)
#define SM_BAR (SM_MISC - 3072)
#define SM_H 65536
#define HPANEL 38912
#define SM_MISC 229376
#define SM_TOTAL (SM_MISC + 256)
#define SM_STAGE 0
#define SM_CNT 21248
#define SM_NIB 22528
#define SM_BASE 27648
#define SM_WTOT 30208
#define SM_WR 30720
static_assert(SM_SRC + CAPP * 2 <= SM_BAR && SM_H + 4 * HPANEL <= SM_BAR, "smem");

__device__ uint4 g_xch[NCTA * NCTA * NCH];
__device__ unsigned g_epoch[NCTA];
#define STAMP(i)
#define STAMPW(i, v)

struct Params {
    const __nv_bfloat16* x; const int* src; const int* dst; const __nv_bfloat16* sh; const __nv_bfloat16* ea;
    const __nv_bfloat16* cg; const __nv_bfloat16* wr; const __nv_bfloat16* wo;
    int N, E, fast; unsigned rate;
};

__device__ __forceinline__ unsigned clk() { unsigned c; asm volatile("mov.u32 %0, %%clock;" : "=r"(c)); return c; }
__device__ __forceinline__ bool elect() { unsigned p; asm volatile("{.reg .pred P; elect.sync _|P, 0xffffffff; selp.u32 %0,1,0,P;}" : "=r"(p)); return p; }
__device__ __forceinline__ bool try_wait(unsigned a) { unsigned ok; asm volatile("{.reg .pred p; mbarrier.try_wait.parity.shared::cta.b64 p,[%1],0; selp.u32 %0,1,0,p;}" : "=r"(ok) : "r"(a) : "memory"); return ok; }
__device__ __forceinline__ void bwait(unsigned a) { if (!try_wait(a)) { for (int i = 0; i < (1 << 22) && !try_wait(a); i++); } }
__device__ __forceinline__ unsigned pin(unsigned x) { unsigned y; asm volatile("mov.u32 %0, %1;" : "=r"(y) : "r"(x)); return y; }
__device__ __forceinline__ void bar_init(unsigned a, unsigned c) { asm volatile("mbarrier.init.shared::cta.b64 [%0], %1;" ::"r"(a), "r"(c) : "memory"); }
__device__ __forceinline__ void bar_expect(unsigned a, unsigned bytes) { asm volatile("mbarrier.arrive.expect_tx.shared::cta.b64 _, [%0], %1;" ::"r"(a), "r"(bytes) : "memory"); }
__device__ __forceinline__ void fence_async() { asm volatile("fence.proxy.async.shared::cta;" ::: "memory"); }
__device__ __forceinline__ void cta_sync() { asm volatile("bar.sync 0, 512;" ::: "memory"); }
__device__ __forceinline__ unsigned lds32(unsigned a) { unsigned v; asm volatile("ld.shared.u32 %0,[%1];" : "=r"(v) : "r"(a) : "memory"); return v; }
__device__ __forceinline__ unsigned lds16(unsigned a) { unsigned v; asm volatile("ld.shared.u16 %0,[%1];" : "=r"(v) : "r"(a) : "memory"); return v; }
__device__ __forceinline__ uint4 lds128(unsigned a) { uint4 v; asm volatile("ld.shared.v4.u32 {%0,%1,%2,%3},[%4];" : "=r"(v.x), "=r"(v.y), "=r"(v.z), "=r"(v.w) : "r"(a) : "memory"); return v; }
__device__ __forceinline__ void sts32(unsigned a, unsigned v) { asm volatile("st.shared.u32 [%0],%1;" ::"r"(a), "r"(v) : "memory"); }
__device__ __forceinline__ void sts16(unsigned a, unsigned v) { asm volatile("st.shared.u16 [%0],%1;" ::"r"(a), "r"(v) : "memory"); }
__device__ __forceinline__ void sts64(unsigned a, unsigned x, unsigned y) { asm volatile("st.shared.v2.u32 [%0],{%1,%2};" ::"r"(a), "r"(x), "r"(y) : "memory"); }
__device__ __forceinline__ void sts128(unsigned a, unsigned x, unsigned y, unsigned z, unsigned w) { asm volatile("st.shared.v4.u32 [%0],{%1,%2,%3,%4};" ::"r"(a), "r"(x), "r"(y), "r"(z), "r"(w) : "memory"); }
__device__ __forceinline__ unsigned atoms_add(unsigned a, unsigned v) { unsigned o; asm volatile("atom.shared.add.u32 %0,[%1],%2;" : "=r"(o) : "r"(a), "r"(v) : "memory"); return o; }
__device__ __forceinline__ void ldsm4t(unsigned* r, unsigned a) { asm volatile("ldmatrix.sync.aligned.m8n8.x4.trans.shared.b16 {%0,%1,%2,%3},[%4];" : "=r"(r[0]), "=r"(r[1]), "=r"(r[2]), "=r"(r[3]) : "r"(a) : "memory"); }
__device__ __forceinline__ void stsm4t(unsigned a, unsigned r0, unsigned r1, unsigned r2, unsigned r3) { asm volatile("stmatrix.sync.aligned.m8n8.x4.trans.shared.b16 [%0],{%1,%2,%3,%4};" ::"r"(a), "r"(r0), "r"(r1), "r"(r2), "r"(r3) : "memory"); }
__device__ __forceinline__ unsigned pack2(float lo, float hi) { unsigned p; asm("cvt.rn.bf16x2.f32 %0,%1,%2;" : "=r"(p) : "f"(hi), "f"(lo)); return p; }
__device__ __forceinline__ void mma1688(float* d, unsigned a0, unsigned a1, unsigned b0) {
    asm("mma.sync.aligned.m16n8k8.row.col.f32.bf16.bf16.f32 {%0,%1,%2,%3},{%4,%5},{%6},{%7,%7,%7,%7};"
        : "=f"(d[0]), "=f"(d[1]), "=f"(d[2]), "=f"(d[3]) : "r"(a0), "r"(a1), "r"(b0), "f"(0.f));
}
__device__ __forceinline__ void mma16816(float* d, const unsigned* a, unsigned b0, unsigned b1) {
    asm("mma.sync.aligned.m16n8k16.row.col.f32.bf16.bf16.f32 {%0,%1,%2,%3},{%4,%5,%6,%7},{%8,%9},{%10,%10,%10,%10};"
        : "=f"(d[0]), "=f"(d[1]), "=f"(d[2]), "=f"(d[3]) : "r"(a[0]), "r"(a[1]), "r"(a[2]), "r"(a[3]), "r"(b0), "r"(b1), "f"(0.f));
}
__device__ __forceinline__ unsigned hfma_lo(unsigned a, unsigned b, unsigned c) {
    __nv_bfloat162 r = __hfma2(*(__nv_bfloat162*)&a, __low2bfloat162(*(__nv_bfloat162*)&b), *(__nv_bfloat162*)&c); return *(unsigned*)&r;
}
__device__ __forceinline__ unsigned hfma_hi(unsigned a, unsigned b, unsigned c) {
    __nv_bfloat162 r = __hfma2(*(__nv_bfloat162*)&a, __high2bfloat162(*(__nv_bfloat162*)&b), *(__nv_bfloat162*)&c); return *(unsigned*)&r;
}
__device__ __forceinline__ void tma_x(unsigned da, const CUtensorMap* tm, unsigned ba, int c1) {
    asm volatile("cp.async.bulk.tensor.3d.shared::cluster.global.mbarrier::complete_tx::bytes [%0], [%1, {%3,%4,%3}], [%2];" ::"r"(da), "l"(tm), "r"(ba), "r"(0), "r"(c1) : "memory");
}
__device__ __forceinline__ void tma_2d(unsigned da, const CUtensorMap* tm, unsigned ba, int c0, int c1) {
    asm volatile("cp.async.bulk.tensor.2d.shared::cluster.global.mbarrier::complete_tx::bytes [%0], [%1, {%3,%4}], [%2];" ::"r"(da), "l"(tm), "r"(ba), "r"(c0), "r"(c1) : "memory");
}
__device__ __forceinline__ void tma_st(const CUtensorMap* tm, unsigned sa, int c0, int c1) {
    asm volatile("cp.async.bulk.tensor.2d.global.shared::cta.bulk_group [%0, {%2,%3}], [%1];" ::"l"(tm), "r"(sa), "r"(c0), "r"(c1) : "memory");
}
__device__ __forceinline__ void pf_l2(const void* p, unsigned bytes) { asm volatile("cp.async.bulk.prefetch.L2.global [%0], %1;" ::"l"(p), "r"(bytes) : "memory"); }
__device__ __forceinline__ unsigned nibsum(unsigned v) { unsigned x = (v & 0x0F0F0F0Fu) + ((v >> 4) & 0x0F0F0F0Fu); return (x * 0x01010101u) >> 24; }

#define WG_REGS24(d) "+f"(d[0]), "+f"(d[1]), "+f"(d[2]), "+f"(d[3]), "+f"(d[4]), "+f"(d[5]), "+f"(d[6]), "+f"(d[7]), \
    "+f"(d[8]), "+f"(d[9]), "+f"(d[10]), "+f"(d[11]), "+f"(d[12]), "+f"(d[13]), "+f"(d[14]), "+f"(d[15]), \
    "+f"(d[16]), "+f"(d[17]), "+f"(d[18]), "+f"(d[19]), "+f"(d[20]), "+f"(d[21]), "+f"(d[22]), "+f"(d[23])
template <int NN> __device__ __forceinline__ void wgmma_rs(float* d, const unsigned* a, uint64_t desc, int scale_d);
template <> __device__ __forceinline__ void wgmma_rs<48>(float* d, const unsigned* a, uint64_t desc, int scale_d) {
    asm volatile("{.reg .pred p; setp.ne.b32 p, %29, 0;\n"
        "wgmma.mma_async.sync.aligned.m64n48k16.f32.bf16.bf16 {%0,%1,%2,%3,%4,%5,%6,%7,%8,%9,%10,%11,%12,%13,%14,%15,%16,%17,%18,%19,"
        "%20,%21,%22,%23}, {%24,%25,%26,%27}, %28, p, 1, 1, 0;}"
        : WG_REGS24(d)
        : "r"(a[0]), "r"(a[1]), "r"(a[2]), "r"(a[3]), "l"(desc), "r"(scale_d));
}
template <> __device__ __forceinline__ void wgmma_rs<64>(float* d, const unsigned* a, uint64_t desc, int scale_d) {
    asm volatile("{.reg .pred p; setp.ne.b32 p, %37, 0;\n"
        "wgmma.mma_async.sync.aligned.m64n64k16.f32.bf16.bf16 {%0,%1,%2,%3,%4,%5,%6,%7,%8,%9,%10,%11,%12,%13,%14,%15,%16,%17,%18,%19,"
        "%20,%21,%22,%23,%24,%25,%26,%27,%28,%29,%30,%31}, {%32,%33,%34,%35}, %36, p, 1, 1, 0;}"
        : WG_REGS24(d), "+f"(d[24]), "+f"(d[25]), "+f"(d[26]), "+f"(d[27]), "+f"(d[28]), "+f"(d[29]), "+f"(d[30]), "+f"(d[31])
        : "r"(a[0]), "r"(a[1]), "r"(a[2]), "r"(a[3]), "l"(desc), "r"(scale_d));
}
__device__ __forceinline__ void wg_fence() { asm volatile("wgmma.fence.sync.aligned;" ::: "memory"); }
__device__ __forceinline__ void wg_commit() { asm volatile("wgmma.commit_group.sync.aligned;" ::: "memory"); }
__device__ __forceinline__ void wg_wait0() { asm volatile("wgmma.wait_group.sync.aligned 0;" ::: "memory"); }

__device__ __forceinline__ void edge_body(unsigned* acc, unsigned xa, unsigned ra, unsigned bf, unsigned ebar) {
#pragma unroll
    for (int h = 0; h < 2; h++) {
        unsigned x0[4], x1[4];
        ldsm4t(x0, xa + h * 1024);
        ldsm4t(x1, xa + h * 1024 + 512);
        uint4 rw = lds128(ra + h * 256);
        float d[4];
        mma1688(d, x0[0], x0[1], bf);
        acc[8 * h + 0] = hfma_lo(pack2(d[0], d[1]), rw.x, acc[8 * h + 0]);
        if (h == 1) { if (elect()) asm volatile("mbarrier.arrive.shared::cta.b64 _, [%0]; // %1" ::"r"(ebar), "r"(acc[8]) : "memory"); }
        acc[8 * h + 1] = hfma_hi(pack2(d[2], d[3]), rw.x, acc[8 * h + 1]);
        mma1688(d, x0[2], x0[3], bf);
        acc[8 * h + 2] = hfma_lo(pack2(d[0], d[1]), rw.y, acc[8 * h + 2]);
        acc[8 * h + 3] = hfma_hi(pack2(d[2], d[3]), rw.y, acc[8 * h + 3]);
        mma1688(d, x1[0], x1[1], bf);
        acc[8 * h + 4] = hfma_lo(pack2(d[0], d[1]), rw.z, acc[8 * h + 4]);
        acc[8 * h + 5] = hfma_hi(pack2(d[2], d[3]), rw.z, acc[8 * h + 5]);
        mma1688(d, x1[2], x1[3], bf);
        acc[8 * h + 6] = hfma_lo(pack2(d[0], d[1]), rw.w, acc[8 * h + 6]);
        acc[8 * h + 7] = hfma_hi(pack2(d[2], d[3]), rw.w, acc[8 * h + 7]);
    }
}

__device__ __forceinline__ void slow_path(const Params& p, unsigned sb) {
    const int lane = threadIdx.x & 31, warp = threadIdx.x >> 5;
#pragma unroll 1
    for (int nl = warp; nl < NPC; nl += 16) {
        const int node = blockIdx.x * NPC + nl;
        float acc[4][8];
#pragma unroll
        for (int w = 0; w < 4; w++)
#pragma unroll
            for (int j = 0; j < 8; j++) acc[w][j] = 0.f;
        if (node < p.N) {
#pragma unroll 1
            for (int e0 = 0; e0 < p.E; e0 += 32) {
                int e = e0 + lane;
                unsigned m = __ballot_sync(~0u, e < p.E && p.dst[e] == node);
                while (m) {
                    int ee = e0 + __ffs(m) - 1; m &= m - 1;
                    int s = p.src[ee];
                    float rw[8];
#pragma unroll
                    for (int j = 0; j < 8; j++) rw[j] = 0.f;
#pragma unroll 1
                    for (int k = 0; k < 16; k++) {
                        float a = __bfloat162float(p.ea[(size_t)ee * 16 + k]);
#pragma unroll
                        for (int j = 0; j < 8; j++) rw[j] += a * __bfloat162float(p.wr[k * 256 + lane * 8 + j]);
                    }
#pragma unroll 1
                    for (int u = 0; u < 4; u++) {
                        float y[8];
#pragma unroll
                        for (int j = 0; j < 8; j++) y[j] = rw[j] * __bfloat162float(p.x[((size_t)s * 4 + u) * 256 + lane * 8 + j]);
#pragma unroll
                        for (int w = 0; w < 4; w++) {
                            float a = 0.f;
#pragma unroll
                            for (int v = 0; v < 4; v++) a += __bfloat162float(p.cg[u * 16 + v * 4 + w]) * __bfloat162float(p.sh[(size_t)ee * 4 + v]);
#pragma unroll
                            for (int j = 0; j < 8; j++) acc[w][j] += a * y[j];
                        }
                    }
                }
            }
        }
#pragma unroll
        for (int w = 0; w < 4; w++) {
            int R = nl * 4 + w;
            sts128(sb + SM_H + (lane >> 3) * HPANEL + R * 128 + (((lane & 7) ^ (R & 7)) << 4),
                   pack2(acc[w][0], acc[w][1]), pack2(acc[w][2], acc[w][3]), pack2(acc[w][4], acc[w][5]), pack2(acc[w][6], acc[w][7]));
        }
    }
}

template <int NN>
__device__ __forceinline__ void out_chunk(float* d, unsigned stg, const CUtensorMap* tmo, int wg, int row0, bool first) {
    const int lane = threadIdx.x & 31, wq = (threadIdx.x >> 5) & 3;
    if (!first) {
        if ((threadIdx.x & 127) == 0) asm volatile("cp.async.bulk.wait_group.read 0;" ::: "memory");
    }
    asm volatile("bar.sync %0, 128;" ::"r"(wg + 1) : "memory");
    const int mi = lane >> 3, r = lane & 7;
    const unsigned a = stg + ((mi >> 1) * 8 + r) * 128 + (((2 * wq + (mi & 1)) ^ r) << 4);
#pragma unroll
    for (int n = 0; n < NN / 8; n += 2)
        stsm4t(a + n * 1024, pack2(d[4 * n], d[4 * n + 1]), pack2(d[4 * n + 2], d[4 * n + 3]), pack2(d[4 * n + 4], d[4 * n + 5]), pack2(d[4 * n + 6], d[4 * n + 7]));
    fence_async();
    asm volatile("bar.sync %0, 128;" ::"r"(wg + 1) : "memory");
    if ((threadIdx.x & 127) == 0) {
#pragma unroll
        for (int j = 0; j < NN / 16; j++) tma_st(tmo, stg + j * 2048, wg * 64, row0 + j * 16);
        asm volatile("cp.async.bulk.commit_group;" ::: "memory");
    }
}

__global__ void __launch_bounds__(512, 1)
mace_kernel(const __grid_constant__ CUtensorMap tmx, const __grid_constant__ CUtensorMap tmw, const __grid_constant__ CUtensorMap tmo,
            const __grid_constant__ Params p) {
    extern __shared__ __align__(1024) char smem_raw[];
    const unsigned tstart = clk();
    unsigned sb;
    asm volatile("mov.u32 %0, %1;" : "=r"(sb) : "r"((unsigned)__cvta_generic_to_shared(smem_raw)));
    const int tid = threadIdx.x, lane = tid & 31, warp = __shfl_sync(~0u, tid >> 5, 0);
    const int cta = blockIdx.x;
    const unsigned wbar = sb + SM_MISC, rbar = sb + SM_MISC + 64, flagA = sb + SM_MISC + 80, tmaxA = sb + SM_MISC + 84;
    bool slow = !p.fast;
    int s0 = 0, nst = 0;
    unsigned T0 = 0;

    if (tid < 9) bar_init(wbar + tid * 8, 1);
    if (!slow) {
        const int e0 = cta * EPC + tid * 4;
        const bool has = tid < EPC / 4 && e0 < p.E;
        int4 s4 = make_int4(0, 0, 0, 0), d4 = s4;
        if (has) { s4 = __ldg((const int4*)(p.src + e0)); d4 = __ldg((const int4*)(p.dst + e0)); }
        unsigned ep;
        asm volatile("ld.volatile.global.u32 %0, [%1];" : "=r"(ep) : "l"(g_epoch + cta));
        if (tid < NCTA) sts32(sb + SM_CNT + tid * 4, 0);
        if (tid < 320) sts128(sb + SM_NIB + tid * 16, 0, 0, 0, 0);
        if (tid < CAPP / 4) { sts128(sb + SM_DESC + tid * 16, 0x7F, 0x7F, 0x7F, 0x7F); sts128(sb + SM_EID + tid * 16, 0, 0, 0, 0); sts64(sb + SM_SRC + tid * 8, 0x80008000u, 0x80008000u); }
        if (tid < 384) bar_init(sb + SM_BAR + tid * 8, (tid & 1) ? 8 : 1);
        if (tid == 0) sts64(flagA, 0, 0);
        asm volatile("fence.mbarrier_init.release.cluster;" ::: "memory");
        fence_async();
        cta_sync();
        STAMP(0);
        if (warp == 15) {
            if (lane == 0) bar_expect(rbar, 8192);
            if (lane < 16) asm volatile("cp.async.bulk.shared::cluster.global.mbarrier::complete_tx::bytes [%0], [%1], 512, [%2];" ::"r"(sb + SM_WR + lane * 528), "l"(p.wr + lane * 256), "r"(rbar) : "memory");
        }
        if (has) {
            const int ss[4] = {s4.x, s4.y, s4.z, s4.w}, dd[4] = {d4.x, d4.y, d4.z, d4.w};
#pragma unroll
            for (int j = 0; j < 4; j++) {
                unsigned c = (unsigned)dd[j] / NPC, dl = dd[j] - c * NPC;
                unsigned slot = atoms_add(sb + SM_CNT + c * 4, 1);
                if (slot < NCH * 3) sts32(sb + SM_STAGE + c * (NCH * 16) + (slot + slot / 3) * 4, ((tid * 4 + j) << 21) | (ss[j] << 7) | dl);
            }
        }
        ep = (ep + 1) & 0xFFFF;
        cta_sync();
        STAMP(1);
        {
            const unsigned el = min((clk() - tstart) >> 4, 0x1FFFu);
#pragma unroll
            for (int k = 0; k < 3; k++) {
                int i = tid + k * 512;
                if (i < NCTA * NCH) {
                    int c = i / NCH, j = i - c * NCH;
                    uint4 v = lds128(sb + SM_STAGE + i * 16);
                    int n = lds32(sb + SM_CNT + c * 4);
                    v.w = (ep << 16) | (el << 3) | (n > NCH * 3 ? 4 : 0) | min(max(n - 3 * j, 0), 3);
                    asm volatile("st.volatile.global.v4.u32 [%0], {%1,%2,%3,%4};" ::"l"(g_xch + (c * NCTA + cta) * NCH + j), "r"(v.x), "r"(v.y), "r"(v.z), "r"(v.w) : "memory");
                }
            }
            if (tid == 0) g_epoch[cta] = ep;
            if (warp == 14) {
                int r = cta + lane * NCTA;
                if (r < PFLEAD && r < p.N) pf_l2(p.x + (size_t)r * 1024, 2048);
            }
            if (warp == 13 && lane < 19) {
                int eb = cta * EPC + lane * 64;
                int n = min(64, p.E - eb);
                if (n > 0) { pf_l2(p.ea + (size_t)eb * 16, n * 32); pf_l2(p.sh + (size_t)eb * 4, n * 8); }
            }
        }
        uint4 rc[3];
        unsigned bad = 0, mx = 0;
        {
            const uint4* q = g_xch + cta * NCTA * NCH + tid;
            const bool h2 = tid + 1024 < NCTA * NCH;
            rc[2] = make_uint4(0, 0, 0, ep << 16);
            while (true) {
                asm volatile("ld.volatile.global.v4.u32 {%0,%1,%2,%3}, [%4];" : "=r"(rc[0].x), "=r"(rc[0].y), "=r"(rc[0].z), "=r"(rc[0].w) : "l"(q) : "memory");
                asm volatile("ld.volatile.global.v4.u32 {%0,%1,%2,%3}, [%4];" : "=r"(rc[1].x), "=r"(rc[1].y), "=r"(rc[1].z), "=r"(rc[1].w) : "l"(q + 512) : "memory");
                if (h2) asm volatile("ld.volatile.global.v4.u32 {%0,%1,%2,%3}, [%4];" : "=r"(rc[2].x), "=r"(rc[2].y), "=r"(rc[2].z), "=r"(rc[2].w) : "l"(q + 1024) : "memory");
                bool ok = (rc[0].w >> 16) == ep && (rc[1].w >> 16) == ep && (rc[2].w >> 16) == ep;
                if (__all_sync(~0u, ok)) break;
                if (__any_sync(~0u, clk() - tstart > 2000000u)) { bad = 1; rc[0].w = rc[1].w = rc[2].w = 0; break; }
            }
        }
        STAMP(2);
        unsigned ord[3];
#pragma unroll
        for (int k = 0; k < 3; k++) {
            const unsigned n = rc[k].w & 3;
            bad |= rc[k].w & 4;
            mx = max(mx, (rc[k].w >> 3) & 0x1FFF);
            const unsigned rr[3] = {rc[k].x, rc[k].y, rc[k].z};
            ord[k] = 0;
#pragma unroll
            for (int j = 0; j < 3; j++) {
                if (j < n) {
                    unsigned sh4 = (rr[j] >> 5) & 28;
                    unsigned o = (atoms_add(sb + SM_NIB + ((rr[j] >> 8) & 0x1FFC), 1u << sh4) >> sh4) & 15;
                    bad |= (o == 15);
                    ord[k] |= o << (4 * j);
                }
            }
        }
        mx = __reduce_max_sync(~0u, mx);
        if (lane == 0) asm volatile("red.shared.max.u32 [%0], %1;" ::"r"(tmaxA), "r"(mx) : "memory");
        if (bad) sts32(flagA, 1);
        cta_sync();
        STAMP(15);
        unsigned c0 = 0, c1 = 0, c2 = 0, c3 = 0, inc = 0;
        if (warp < 10) {
            uint4 v = lds128(sb + SM_NIB + tid * 16);
            c0 = nibsum(v.x); c1 = c0 + nibsum(v.y); c2 = c1 + nibsum(v.z); c3 = c2 + nibsum(v.w);
            inc = c3;
#pragma unroll
            for (int o = 1; o < 32; o <<= 1) { unsigned t = __shfl_up_sync(~0u, inc, o); if (lane >= o) inc += t; }
            if (lane == 31) sts32(sb + SM_WTOT + warp * 4, inc);
        }
        cta_sync();
        {
            unsigned wt = lane < 10 ? lds32(sb + SM_WTOT + lane * 4) : 0;
            const unsigned total = __reduce_add_sync(~0u, wt);
            const unsigned before = __reduce_add_sync(~0u, lane < warp ? wt : 0);
            slow = lds32(flagA) != 0 || total > CAP;
            const int ns = (total + 7) >> 3;
            s0 = (NS - ns % NS) % NS;
            nst = s0 + ns;
            T0 = tstart + (lds32(tmaxA) << 4) + T0DELTA;
            if (warp < 10) {
                unsigned ex = before + inc - c3 + 8 * s0;
                sts64(sb + SM_BASE + tid * 8, ex | ((ex + c0) << 16), (ex + c1) | ((ex + c2) << 16));
            }
        }
        cta_sync();
        if (!slow) {
#pragma unroll
            for (int k = 0; k < 3; k++) {
                const unsigned n = rc[k].w & 3;
                const unsigned rr[3] = {rc[k].x, rc[k].y, rc[k].z};
                const unsigned ebase = ((tid + k * 512) / NCH) * EPC;
#pragma unroll
                for (int j = 0; j < 3; j++) {
                    if (j < n) {
                        unsigned sh4 = (rr[j] >> 5) & 28, w4 = (rr[j] >> 8) & 0x1FFC;
                        unsigned o = (ord[k] >> (4 * j)) & 15;
                        unsigned pos = lds16(sb + SM_BASE + (w4 >> 1)) + nibsum(lds32(sb + SM_NIB + w4) & ((1u << sh4) - 1)) + o;
                        unsigned back = min(o, pos & 7);
                        unsigned st = pos >> 3;
                        unsigned ri = (st % NS) * 8 + (pos & 7);
                        sts32(sb + SM_DESC + pos * 4, (st << 24) | (ri << 17) | ((ri - back) << 10) | (rr[j] & 0x7F));
                        sts32(sb + SM_EID + pos * 4, ebase + (rr[j] >> 21));
                        sts16(sb + SM_SRC + pos * 2, ((rr[j] >> 7) & 0x3FFF) | (back ? 0x8000 : 0));
                    }
                }
            }
        }
        bwait(rbar);
    }

    if (slow) {
        asm volatile("fence.mbarrier_init.release.cluster;" ::: "memory");
        fence_async();
        cta_sync();
        if (tid < 4) { bar_expect(wbar + tid * 8, 16384); tma_2d(sb + tid * 16384, &tmw, wbar + tid * 8, tid * 64, 0); }
        slow_path(p, sb);
    } else if (warp < NCONS) {
        fence_async();
        cta_sync();
        STAMP(3);
        unsigned acc[6][16];
#pragma unroll
        for (int k = 0; k < 6; k++)
#pragma unroll
            for (int j = 0; j < 16; j++) acc[k][j] = 0;
        const int g = lane >> 2, t = lane & 3;
        const unsigned xoff = (lane & 3) * 128 + ((((lane >> 3) + (lane & 4)) ^ (lane & 3)) << 4);
        const unsigned xl = pin(sb + SM_X + xoff);
        const unsigned rl = pin(sb + SM_R + (t >> 1) * 128 + ((g ^ (4 * (t >> 1))) << 4));
        const unsigned cl = pin((t >> 1) == (g >> 2) ? sb + SM_R + 512 + (2 * (g & 3) + (t & 1)) * 4 : 0);
        const unsigned w6 = warp * 6;
        unsigned bf = 0;
        unsigned da = sb + SM_DESC + (s0 >> 2) * 128 + lane * 4;
        unsigned v = lds32(da);
        for (int r = ((nst + 3) >> 2) - (s0 >> 2); r > 0; r--) {
            unsigned my = ((v & 0x7F) - w6 < 6u) ? v - w6 : ~0u;
            da += 128;
            v = lds32(da);
            while (true) {
                const unsigned val = __reduce_min_sync(~0u, my);
                if (val == ~0u) break;
                if (my == val) my = ~0u;
                const unsigned bar = sb + SM_BAR + ((val >> 20) & 0xFF0);
                const unsigned ro = ((val >> 17) & 0x7F) * RSTR;
                const unsigned xa = xl + ((val << 1) & 0x3F800);
                bwait(bar);
                asm volatile("{.reg .pred p; setp.ne.u32 p,%2,0; @p ld.shared.u32 %0,[%1];}" : "+r"(bf) : "r"(cl + ro), "r"(cl) : "memory");
                switch (val & 7) {
                    case 0: edge_body(acc[0], xa, rl + ro, bf, bar + 8); break;
                    case 1: edge_body(acc[1], xa, rl + ro, bf, bar + 8); break;
                    case 2: edge_body(acc[2], xa, rl + ro, bf, bar + 8); break;
                    case 3: edge_body(acc[3], xa, rl + ro, bf, bar + 8); break;
                    case 4: edge_body(acc[4], xa, rl + ro, bf, bar + 8); break;
                    default: edge_body(acc[5], xa, rl + ro, bf, bar + 8); break;
                }
            }
        }
        cta_sync();
        STAMP(4);
        const unsigned ha = xl + (SM_H - SM_X) + w6 * 512;
#pragma unroll
        for (int k = 0; k < 6; k++) {
            if (w6 + k < NPC) {
#pragma unroll
                for (int b = 0; b < 4; b++)
                    stsm4t((ha ^ (((b ^ k) & 1) * 64)) + k * 512 + b * HPANEL, acc[k][4 * b], acc[k][4 * b + 1], acc[k][4 * b + 2], acc[k][4 * b + 3]);
            }
        }
    } else {
        const int g = lane >> 2, t = lane & 3, hw = warp - NCONS;
        unsigned wf[16][4];
        {
            const int mi = lane >> 3, r = lane & 7;
            const unsigned a = sb + SM_WR + (4 * (r >> 1) + (r & 1) + 2 * (mi >> 1)) * 528;
#pragma unroll
            for (int q = 0; q < 16; q++) {
                const int h = q >> 3, th = (q >> 2) & 1, i = q & 3, b = 2 * h + (i >> 1);
                const int ch = 64 * b + 8 * ((2 * (i & 1) + 4 * th) ^ (4 * (b & 1)));
                ldsm4t(wf[q], a + ch * 2 + (mi & 1) * 16);
            }
        }
        unsigned cg0 = 0, cg1 = 0;
        if (t < 2) {
            const unsigned short* cg = (const unsigned short*)p.cg;
            const int o = (2 * (g & 1)) * 16 + 2 * t * 4 + (g >> 1);
            cg0 = cg[o] | ((unsigned)cg[o + 4] << 16);
            cg1 = cg[o + 16] | ((unsigned)cg[o + 20] << 16);
        }
        fence_async();
        cta_sync();
        const int eg = (g >> 1) + 4 * (g & 1);
        const char* eap = (const char*)p.ea + t * 8;
        const char* shp = (const char*)p.sh + (t & 1) * 4;
        const unsigned rs0 = sb + SM_R + t * RSTR + g * 16, rs1 = sb + SM_R + t * RSTR + 128 + ((g ^ 4) << 4), cs = sb + SM_R + t * RSTR + 512 + g * 4;
        const unsigned rate = p.rate, zero = p.fast - 1;
        int s = s0 + hw, slot = s % NS;
        int pfr = cta + ((PFLEAD - cta + NCTA - 1) / NCTA + hw) * NCTA;
        const int N = p.N;
        unsigned b0, b1, sv;
        {
            unsigned eid = lds32(sb + SM_EID + (s * 8 + eg) * 4);
            asm volatile("ld.global.nc.v2.u32 {%0,%1}, [%2];" : "=r"(b0), "=r"(b1) : "l"(eap + (size_t)eid * 32));
            asm volatile("ld.global.nc.u32 %0, [%1];" : "=r"(sv) : "l"(shp + (size_t)eid * 8));
        }
        for (; s < nst; s += 3) {
            const uint4 k4 = lds128(sb + SM_SRC + s * 16);
            const unsigned eidn = lds32(sb + SM_EID + (s * 8 + 24 + eg) * 4);
            const unsigned full = sb + SM_BAR + s * 16;
            const unsigned kk[4] = {k4.x, k4.y, k4.z, k4.w};
            if (s - NS >= s0) bwait(full - NS * 16 + 8);
            const unsigned xs = sb + SM_X + slot * 16384;
#pragma unroll
            for (int j0 = 0; j0 < 8; j0 += GRP) {
                const unsigned ka = (kk[j0 >> 1] >> ((j0 & 1) * 16)) & 0x3FFF, kb = (kk[(j0 + GRP - 1) >> 1] >> (((j0 + GRP - 1) & 1) * 16)) & 0x3FFF;
                const unsigned dl = T0 + (((ka + max(ka, kb)) * rate) >> 9);
                unsigned now = clk();
                while ((int)(now - dl) < 0) now = clk();
                if (elect()) {
#pragma unroll
                    for (int j = j0; j < j0 + GRP; j++) {
                        const unsigned k = (kk[j >> 1] >> ((j & 1) * 16)) & 0xFFFF;
                        if (k < 0x8000) tma_x(xs + j * 2048, &tmx, full, k * 4);
                    }
                }
            }
            const unsigned nrow = 8 - __popc((k4.x & 0x80008000u) | ((k4.y & 0x80008000u) >> 1) | ((k4.z & 0x80008000u) >> 2) | ((k4.w & 0x80008000u) >> 3));
            if (pfr < (int)(k4.x & 0x3FFF) + PFLEAD && pfr < N) { if (elect()) pf_l2(p.x + (size_t)pfr * 1024, 2048); pfr += 3 * NCTA; }
            const unsigned ro = slot * 8 * RSTR;
            const unsigned c0 = b0 + zero, c1 = b1 + zero, cv = t < 2 ? sv : 0;
            asm volatile("ld.global.nc.v2.u32 {%0,%1}, [%2];" : "=r"(b0), "=r"(b1) : "l"(eap + (size_t)eidn * 32));
            asm volatile("ld.global.nc.u32 %0, [%1];" : "=r"(sv) : "l"(shp + (size_t)eidn * 8));
            {
                float d[4];
                mma1688(d, cg0, cg1, cv);
                sts32(cs + ro, pack2(d[0], d[2]));
                sts32(cs + ro + 4 * RSTR, pack2(d[1], d[3]));
            }
#pragma unroll
            for (int q4 = 0; q4 < 4; q4++) {
                float d[4][4];
#pragma unroll
                for (int i = 0; i < 4; i++) mma16816(d[i], wf[q4 * 4 + i], c0, c1);
                const unsigned a = ((q4 & 1) ? rs1 : rs0) + ro + (q4 >> 1) * 256;
                sts128(a, pack2(d[0][0], d[0][2]), pack2(d[1][0], d[1][2]), pack2(d[2][0], d[2][2]), pack2(d[3][0], d[3][2]));
                sts128(a + 4 * RSTR, pack2(d[0][1], d[0][3]), pack2(d[1][1], d[1][3]), pack2(d[2][1], d[2][3]), pack2(d[3][1], d[3][3]));
            }
            __syncwarp();
            if (elect()) bar_expect(full, nrow * 2048);
            slot += 3; if (slot >= NS) slot -= NS;
        }
        for (; s < nst + 4; s += 3) {
            if (s - NS >= s0) bwait(sb + SM_BAR + (s - NS) * 16 + 8);
            const int i = s - nst;
            if (elect()) { bar_expect(wbar + i * 8, 16384); tma_2d(sb + i * 16384, &tmw, wbar + i * 8, i * 64, 0); }
        }
        cta_sync();
    }

    const int wg = warp >> 2, wq = warp & 3;
    unsigned af[16][4];
    const unsigned wt = sb + wg * 16384;
    const unsigned wa = wt + (((lane >> 4) * 8 + (lane & 7)) << 7) + (((2 * wq + ((lane >> 3) & 1)) ^ (lane & 7)) << 4);
    bwait(wbar + wg * 8);
#pragma unroll
    for (int k = 0; k < 8; k++) ldsm4t(af[k], wa + k * 2048);
    fence_async();
    cta_sync();
    STAMP(5);
    if ((tid & 127) == 0) { bar_expect(wbar + 32 + wg * 8, 16384); tma_2d(wt, &tmw, wbar + 32 + wg * 8, wg * 64, 128); }
    const uint64_t desc0 = (uint64_t)(((sb + SM_H) >> 4) & 0x3FFF) | (1ull << 16) | (64ull << 32) | (1ull << 62);
    float d[32];
    const int row0 = cta * (NPC * 4);
    wg_fence();
#pragma unroll
    for (int k = 0; k < 8; k++) wgmma_rs<64>(d, af[k], desc0 + (k >> 2) * (HPANEL >> 4) + (k & 3) * 2, k != 0);
    wg_commit();
    bwait(wbar + 32 + wg * 8);
#pragma unroll
    for (int k = 0; k < 8; k++) ldsm4t(af[8 + k], wa + k * 2048);
    wg_fence();
#pragma unroll
    for (int k = 8; k < 16; k++) wgmma_rs<64>(d, af[k], desc0 + (k >> 2) * (HPANEL >> 4) + (k & 3) * 2, 1);
    wg_commit();
    wg_wait0();
    out_chunk<64>(d, wt, &tmo, wg, row0, true);
#pragma unroll 1
    for (int c = 1; c < 4; c++) {
        wg_fence();
#pragma unroll
        for (int k = 0; k < 16; k++) wgmma_rs<64>(d, af[k], desc0 + c * 512 + (k >> 2) * (HPANEL >> 4) + (k & 3) * 2, k != 0);
        wg_commit();
        wg_wait0();
        out_chunk<64>(d, wt, &tmo, wg, row0 + c * 64, false);
    }
    wg_fence();
#pragma unroll
    for (int k = 0; k < 16; k++) wgmma_rs<48>(d, af[k], desc0 + 4 * 512 + (k >> 2) * (HPANEL >> 4) + (k & 3) * 2, k != 0);
    wg_commit();
    wg_wait0();
    out_chunk<48>(d, wt, &tmo, wg, row0 + 256, false);
    if ((tid & 127) == 0) asm volatile("cp.async.bulk.wait_group.read 0;" ::: "memory");
    STAMP(6);
}

typedef CUresult (*EncFn)(CUtensorMap*, CUtensorMapDataType, cuuint32_t, void*, const cuuint64_t*, const cuuint64_t*, const cuuint32_t*,
                          const cuuint32_t*, CUtensorMapInterleave, CUtensorMapSwizzle, CUtensorMapL2promotion, CUtensorMapFloatOOBfill);

extern "C" void kernel_launch(void* const* d_in, const int* in_sizes, int n_in, void* d_out, int out_size) {
    static EncFn enc = nullptr;
    static int nsm = 0;
    if (!enc) {
        void* fn = nullptr; cudaDriverEntryPointQueryResult qr;
        cudaGetDriverEntryPoint("cuTensorMapEncodeTiled", &fn, cudaEnableDefault, &qr);
        enc = (EncFn)fn;
        int dev = 0; cudaGetDevice(&dev);
        cudaDeviceGetAttribute(&nsm, cudaDevAttrMultiProcessorCount, dev);
        cudaFuncSetAttribute(mace_kernel, cudaFuncAttributeMaxDynamicSharedMemorySize, SM_TOTAL);
    }
    Params p;
    p.x = (const __nv_bfloat16*)d_in[0]; p.src = (const int*)d_in[1]; p.dst = (const int*)d_in[2];
    p.sh = (const __nv_bfloat16*)d_in[3]; p.ea = (const __nv_bfloat16*)d_in[4]; p.cg = (const __nv_bfloat16*)d_in[5];
    p.wr = (const __nv_bfloat16*)d_in[6]; p.wo = (const __nv_bfloat16*)d_in[7];
    p.N = in_sizes[0] / 1024; p.E = in_sizes[1];
    p.fast = (nsm >= NCTA && p.N <= NCTA * NPC && p.E <= NCTA * EPC && p.E > 0 && (p.E & 3) == 0) ? 1 : 0;
    p.rate = (unsigned)((double)PACE * ((double)p.E / 160000.0) * 256.0 / (double)p.N);
    CUtensorMap tmx, tmw, tmo;
    const cuuint32_t es[3] = {1, 1, 1};
    {
        cuuint64_t dims[3] = {64, (cuuint64_t)p.N * 4, 4}; cuuint64_t str[2] = {512, 128}; cuuint32_t box[3] = {64, 4, 4};
        enc(&tmx, CU_TENSOR_MAP_DATA_TYPE_BFLOAT16, 3, d_in[0], dims, str, box, es, CU_TENSOR_MAP_INTERLEAVE_NONE, CU_TENSOR_MAP_SWIZZLE_128B, CU_TENSOR_MAP_L2_PROMOTION_NONE, CU_TENSOR_MAP_FLOAT_OOB_FILL_NONE);
    }
    {
        cuuint64_t dims[2] = {256, 256}; cuuint64_t str[1] = {512}; cuuint32_t box[2] = {64, 128};
        enc(&tmw, CU_TENSOR_MAP_DATA_TYPE_BFLOAT16, 2, d_in[7], dims, str, box, es, CU_TENSOR_MAP_INTERLEAVE_NONE, CU_TENSOR_MAP_SWIZZLE_128B, CU_TENSOR_MAP_L2_PROMOTION_NONE, CU_TENSOR_MAP_FLOAT_OOB_FILL_NONE);
    }
    {
        cuuint64_t dims[2] = {256, (cuuint64_t)p.N * 4}; cuuint64_t str[1] = {512}; cuuint32_t box[2] = {64, 16};
        enc(&tmo, CU_TENSOR_MAP_DATA_TYPE_BFLOAT16, 2, d_out, dims, str, box, es, CU_TENSOR_MAP_INTERLEAVE_NONE, CU_TENSOR_MAP_SWIZZLE_128B, CU_TENSOR_MAP_L2_PROMOTION_NONE, CU_TENSOR_MAP_FLOAT_OOB_FILL_NONE);
    }
    const int grid = p.fast ? NCTA : (p.N + NPC - 1) / NPC;
    mace_kernel<<<grid, 512, SM_TOTAL>>>(tmx, tmw, tmo, p);
}
```

```cpp
#include <cuda_runtime.h>
#include <cuda_bf16.h>
#include <cuda.h>
#include <stdint.h>

#define NX 10
#define NR 6
#define PACE 44000
#define T0DELTA 11500
#define POLLT 6000
#define PFLEAD 8
#define RSPL 4
#define DISP 1
#define XST "st.relaxed.gpu.global.v4.u32"
#define NCTA 132
#define NPC 76
#define EPC 1216
#define NCH 10
#define CAP 1376
#define CAPP 1440
#define NCONS 13
#define RSTR 544
#define BW 45

#define SB 1024
#define SM_X SB
#define SM_R (SM_X + NX * 16384)
#define SM_EID (SM_R + NR * 8 * RSTR)
#define SM_NEXT (SM_EID + CAPP * 4)
#define SM_H (SB + 65536)
#define HPANEL 38912
#define SM_FULL (SM_H + 4 * HPANEL)
#define SM_EMPTY (SM_FULL + CAPP + 128)
#define SM_SRC (SM_EMPTY + CAPP)
#define SM_BITS (SM_SRC + CAPP * 2)
#define SM_MISC (SM_BITS + 2352)
#define SM_TOTAL (SM_MISC + 128 - SB)
#define SM_STAGE SB
#define SM_CNT (SB + 21248)
#define SM_NIB (SB + 22528)
#define SM_BASE (SB + 27648)
#define SM_WTOT (SB + 30208)
#define SM_WR (SB + 30720)
static_assert(SM_NEXT + CAPP * 4 <= SM_FULL && SM_TOTAL <= 232448, "smem");
#define STR_(x) #x
#define STR(x) STR_(x)

__device__ uint4 g_xch[NCTA * NCTA * NCH];
__device__ unsigned g_epoch[NCTA];
#define STAMP(i)
#define STAMPW(i, v)

struct Params {
    const __nv_bfloat16* x; const int* src; const int* dst; const __nv_bfloat16* sh; const __nv_bfloat16* ea;
    const __nv_bfloat16* cg; const __nv_bfloat16* wr; const __nv_bfloat16* wo;
    int N, E, fast; unsigned rate, zero;
};

__device__ __forceinline__ unsigned clk() { unsigned c; asm volatile("mov.u32 %0, %%clock;" : "=r"(c)); return c; }
__device__ __forceinline__ bool elect() { unsigned p; asm volatile("{.reg .pred P; elect.sync _|P, 0xffffffff; selp.u32 %0,1,0,P;}" : "=r"(p)); return p; }
__device__ __forceinline__ bool try_wait(unsigned a) { unsigned ok; asm volatile("{.reg .pred p; mbarrier.try_wait.parity.shared::cta.b64 p,[%1],0; selp.u32 %0,1,0,p;}" : "=r"(ok) : "r"(a) : "memory"); return ok; }
__device__ __forceinline__ void bwait(unsigned a) { if (!try_wait(a)) { for (int i = 0; i < (1 << 22) && !try_wait(a); i++); } }
__device__ __forceinline__ unsigned pin(unsigned x) { unsigned y; asm volatile("mov.u32 %0, %1;" : "=r"(y) : "r"(x)); return y; }
__device__ __forceinline__ const char* pin64(const char* x) { const char* y; asm volatile("mov.u64 %0, %1;" : "=l"(y) : "l"(x)); return y; }
__device__ __forceinline__ void split(unsigned x, unsigned c) { asm volatile("{.reg .pred p; setp.eq.u32 p, %0, %1; @p exit;}" ::"r"(x), "r"(c) : "memory"); }
__device__ __forceinline__ void bar_init(unsigned a, unsigned c) { asm volatile("mbarrier.init.shared::cta.b64 [%0], %1;" ::"r"(a), "r"(c) : "memory"); }
__device__ __forceinline__ void bar_expect(unsigned a, unsigned bytes) { asm volatile("mbarrier.arrive.expect_tx.shared::cta.b64 _, [%0], %1;" ::"r"(a), "r"(bytes) : "memory"); }
__device__ __forceinline__ void bar_complete(unsigned a, unsigned bytes) { asm volatile("mbarrier.complete_tx.relaxed.cta.shared::cta.b64 [%0], %1;" ::"r"(a), "r"(bytes) : "memory"); }
__device__ __forceinline__ void fence_async() { asm volatile("fence.proxy.async.shared::cta;" ::: "memory"); }
__device__ __forceinline__ void cta_sync() { asm volatile("bar.sync 0, 512;" ::: "memory"); }
__device__ __forceinline__ unsigned lds32(unsigned a) { unsigned v; asm volatile("ld.shared.u32 %0,[%1];" : "=r"(v) : "r"(a) : "memory"); return v; }
__device__ __forceinline__ unsigned lds16(unsigned a) { unsigned v; asm volatile("ld.shared.u16 %0,[%1];" : "=r"(v) : "r"(a) : "memory"); return v; }
__device__ __forceinline__ uint4 lds128(unsigned a) { uint4 v; asm volatile("ld.shared.v4.u32 {%0,%1,%2,%3},[%4];" : "=r"(v.x), "=r"(v.y), "=r"(v.z), "=r"(v.w) : "r"(a) : "memory"); return v; }
__device__ __forceinline__ void sts32(unsigned a, unsigned v) { asm volatile("st.shared.u32 [%0],%1;" ::"r"(a), "r"(v) : "memory"); }
__device__ __forceinline__ void sts16(unsigned a, unsigned v) { asm volatile("st.shared.u16 [%0],%1;" ::"r"(a), "r"(v) : "memory"); }
__device__ __forceinline__ void sts64(unsigned a, unsigned x, unsigned y) { asm volatile("st.shared.v2.u32 [%0],{%1,%2};" ::"r"(a), "r"(x), "r"(y) : "memory"); }
__device__ __forceinline__ void sts128(unsigned a, unsigned x, unsigned y, unsigned z, unsigned w) { asm volatile("st.shared.v4.u32 [%0],{%1,%2,%3,%4};" ::"r"(a), "r"(x), "r"(y), "r"(z), "r"(w) : "memory"); }
__device__ __forceinline__ unsigned atoms_add(unsigned a, unsigned v) { unsigned o; asm volatile("atom.shared.add.u32 %0,[%1],%2;" : "=r"(o) : "r"(a), "r"(v) : "memory"); return o; }
__device__ __forceinline__ void reds_or(unsigned a, unsigned v) { asm volatile("red.shared.or.b32 [%0],%1;" ::"r"(a), "r"(v) : "memory"); }
__device__ __forceinline__ void ldsm4t(unsigned* r, unsigned a) { asm volatile("ldmatrix.sync.aligned.m8n8.x4.trans.shared.b16 {%0,%1,%2,%3},[%4];" : "=r"(r[0]), "=r"(r[1]), "=r"(r[2]), "=r"(r[3]) : "r"(a) : "memory"); }
__device__ __forceinline__ void stsm4t(unsigned a, unsigned r0, unsigned r1, unsigned r2, unsigned r3) { asm volatile("stmatrix.sync.aligned.m8n8.x4.trans.shared.b16 [%0],{%1,%2,%3,%4};" ::"r"(a), "r"(r0), "r"(r1), "r"(r2), "r"(r3) : "memory"); }
__device__ __forceinline__ unsigned pack2(float lo, float hi) { unsigned p; asm("cvt.rn.bf16x2.f32 %0,%1,%2;" : "=r"(p) : "f"(hi), "f"(lo)); return p; }
__device__ __forceinline__ void mma1688(float* d, unsigned a0, unsigned a1, unsigned b0) {
    asm("mma.sync.aligned.m16n8k8.row.col.f32.bf16.bf16.f32 {%0,%1,%2,%3},{%4,%5},{%6},{%7,%7,%7,%7};"
        : "=f"(d[0]), "=f"(d[1]), "=f"(d[2]), "=f"(d[3]) : "r"(a0), "r"(a1), "r"(b0), "f"(0.f));
}
__device__ __forceinline__ void mma16816(float* d, const unsigned* a, unsigned b0, unsigned b1) {
    asm volatile("mma.sync.aligned.m16n8k16.row.col.f32.bf16.bf16.f32 {%0,%1,%2,%3},{%4,%5,%6,%7},{%8,%9},{%10,%10,%10,%10};"
        : "=f"(d[0]), "=f"(d[1]), "=f"(d[2]), "=f"(d[3]) : "r"(a[0]), "r"(a[1]), "r"(a[2]), "r"(a[3]), "r"(b0), "r"(b1), "f"(0.f));
}
__device__ __forceinline__ void tma_x(unsigned da, const void* tm, unsigned ba, int c1) {
    asm volatile("cp.async.bulk.tensor.3d.shared::cluster.global.mbarrier::complete_tx::bytes [%0], [%1, {%3,%4,%3}], [%2];" ::"r"(da), "l"(tm), "r"(ba), "r"(0), "r"(c1) : "memory");
}
__device__ __forceinline__ void tma_2d(unsigned da, const CUtensorMap* tm, unsigned ba, int c0, int c1) {
    asm volatile("cp.async.bulk.tensor.2d.shared::cluster.global.mbarrier::complete_tx::bytes [%0], [%1, {%3,%4}], [%2];" ::"r"(da), "l"(tm), "r"(ba), "r"(c0), "r"(c1) : "memory");
}
__device__ __forceinline__ void tma_st(const CUtensorMap* tm, unsigned sa, int c0, int c1) {
    asm volatile("cp.async.bulk.tensor.2d.global.shared::cta.bulk_group [%0, {%2,%3}], [%1];" ::"l"(tm), "r"(sa), "r"(c0), "r"(c1) : "memory");
}
__device__ __forceinline__ void pf_l2(const void* p, unsigned bytes) { asm volatile("cp.async.bulk.prefetch.L2.global [%0], %1;" ::"l"(p), "r"(bytes) : "memory"); }
__device__ __forceinline__ unsigned nibsum(unsigned v) { unsigned x = (v & 0x0F0F0F0Fu) + ((v >> 4) & 0x0F0F0F0Fu); return (x * 0x01010101u) >> 24; }

#define WG_REGS24(d) "+f"(d[0]), "+f"(d[1]), "+f"(d[2]), "+f"(d[3]), "+f"(d[4]), "+f"(d[5]), "+f"(d[6]), "+f"(d[7]), \
    "+f"(d[8]), "+f"(d[9]), "+f"(d[10]), "+f"(d[11]), "+f"(d[12]), "+f"(d[13]), "+f"(d[14]), "+f"(d[15]), \
    "+f"(d[16]), "+f"(d[17]), "+f"(d[18]), "+f"(d[19]), "+f"(d[20]), "+f"(d[21]), "+f"(d[22]), "+f"(d[23])
template <int NN> __device__ __forceinline__ void wgmma_rs(float* d, const unsigned* a, uint64_t desc, int scale_d);
template <> __device__ __forceinline__ void wgmma_rs<48>(float* d, const unsigned* a, uint64_t desc, int scale_d) {
    asm volatile("{.reg .pred p; setp.ne.b32 p, %29, 0;\n"
        "wgmma.mma_async.sync.aligned.m64n48k16.f32.bf16.bf16 {%0,%1,%2,%3,%4,%5,%6,%7,%8,%9,%10,%11,%12,%13,%14,%15,%16,%17,%18,%19,"
        "%20,%21,%22,%23}, {%24,%25,%26,%27}, %28, p, 1, 1, 0;}"
        : WG_REGS24(d)
        : "r"(a[0]), "r"(a[1]), "r"(a[2]), "r"(a[3]), "l"(desc), "r"(scale_d));
}
template <> __device__ __forceinline__ void wgmma_rs<64>(float* d, const unsigned* a, uint64_t desc, int scale_d) {
    asm volatile("{.reg .pred p; setp.ne.b32 p, %37, 0;\n"
        "wgmma.mma_async.sync.aligned.m64n64k16.f32.bf16.bf16 {%0,%1,%2,%3,%4,%5,%6,%7,%8,%9,%10,%11,%12,%13,%14,%15,%16,%17,%18,%19,"
        "%20,%21,%22,%23,%24,%25,%26,%27,%28,%29,%30,%31}, {%32,%33,%34,%35}, %36, p, 1, 1, 0;}"
        : WG_REGS24(d), "+f"(d[24]), "+f"(d[25]), "+f"(d[26]), "+f"(d[27]), "+f"(d[28]), "+f"(d[29]), "+f"(d[30]), "+f"(d[31])
        : "r"(a[0]), "r"(a[1]), "r"(a[2]), "r"(a[3]), "l"(desc), "r"(scale_d));
}
__device__ __forceinline__ void wg_fence() { asm volatile("wgmma.fence.sync.aligned;" ::: "memory"); }
__device__ __forceinline__ void wg_commit() { asm volatile("wgmma.commit_group.sync.aligned;" ::: "memory"); }
__device__ __forceinline__ void wg_wait0() { asm volatile("wgmma.wait_group.sync.aligned 0;" ::: "memory"); }

#define PF(D, RW, K, J0, J1) \
    "cvt.rn.bf16x2.f32 t0, " #D "1, " #D "0;\n cvt.rn.bf16x2.f32 t1, " #D "3, " #D "2;\n" \
    "mov.b32 {lo, hi}, " #RW ";\n mov.b32 u0, {lo, lo};\n mov.b32 u1, {hi, hi};\n" \
    "fma.rn.bf16x2 a" #K "_" #J0 ", t0, u0, a" #K "_" #J0 ";\n fma.rn.bf16x2 a" #K "_" #J1 ", t1, u1, a" #K "_" #J1 ";\n"
#define MMA(D, A0, A1) "mma.sync.aligned.m16n8k8.row.col.f32.bf16.bf16.f32 {" #D "0," #D "1," #D "2," #D "3}, {" #A0 "," #A1 "}, {bf}, {fz,fz,fz,fz};\n"
#define LDX(X, OFF) "ldmatrix.sync.aligned.m8n8.x4.trans.shared.b16 {" #X "0," #X "1," #X "2," #X "3}, [xa+" STR(SM_X) "+" #OFF "];\n"
#define DECODE \
    "lop3.b32 xa, dn, 0x3F800, %1, 0xEA;\n" \
    "shr.u32 t2, dn, 21;\n mad.lo.u32 ra, t2, 32, %2;\n mad.lo.u32 ca, t2, 32, %3;\n" \
    "and.b32 t3, dn, 0x7FF;\n shl.b32 t3, t3, 2;\n" SETD
#define LOADS \
    LDX(x, 0) LDX(y, 512) \
    "@act ld.shared.u32 bf, [ca+" STR(SM_R) "];\n" \
    "ld.shared.v4.u32 {r0,r1,r2,r3}, [ra+" STR(SM_R) "];\n" \
    "ld.shared.u32 dn, [t3+" STR(SM_NEXT) "];\n"
#define SETD "and.b32 ix, dn, 0x40000;\n setp.ne.u32 q0, ix, 0;\n and.b32 ix, dn, 0x80000;\n setp.ne.u32 q1, ix, 0;\n and.b32 ix, dn, 0x100000;\n setp.ne.u32 q2, ix, 0;\n"
#define DISPATCH "@q2 bra.uni T45;\n @q1 bra.uni T23;\n @q0 bra.uni B1;\n bra.uni B0;\n"
#define T23 "T23:\n @q0 bra.uni B3;\n"
#define T45 "T45:\n @q1 bra.uni FIN;\n @q0 bra.uni B5;\n"
#define BODY(K) "B" #K ":\n" \
    MMA(d, x0, x1) MMA(e, x2, x3) LDX(x, 1024) \
    "and.b32 bn, dn, 0x7F8;\n" \
    "mbarrier.test_wait.parity.shared::cta.b64 p, [bn+" STR(SM_FULL) "], 0;\n" \
    PF(d, r0, K, 0, 1) MMA(d, y0, y1) PF(e, r1, K, 2, 3) MMA(e, y2, y3) LDX(y, 1536) \
    "ld.shared.v4.u32 {s0,s1,s2,s3}, [ra+" STR(SM_R) "+256];\n" \
    PF(d, r2, K, 4, 5) MMA(d, x0, x1) PF(e, r3, K, 6, 7) MMA(e, x2, x3) \
    PF(d, s0, K, 8, 9) MMA(d, y0, y1) \
    "@l0 mbarrier.arrive.shared::cta.b64 _, [bc+" STR(SM_EMPTY) "];\n" \
    PF(e, s1, K, 10, 11) MMA(e, y2, y3) \
    "mov.u32 bc, bn;\n" DECODE \
    "@!p bra.uni W" #K ";\n" \
    "R" #K ":\n" LOADS \
    PF(d, s2, K, 12, 13) PF(e, s3, K, 14, 15) DISPATCH
#define WAIT(K) "W" #K ":\n mov.u32 t0, 0;\n" \
    "V" #K ":\n mbarrier.try_wait.parity.shared::cta.b64 p, [bc+" STR(SM_FULL) "], 0;\n @p bra.uni R" #K ";\n" \
    "add.u32 t0, t0, 1;\n setp.lt.u32 p, t0, 4000000;\n @p bra.uni V" #K ";\n bra.uni R" #K ";\n"
#define Z4(K, A, B, C, D) "mov.u32 a" #K "_" #A ", 0; mov.u32 a" #K "_" #B ", 0; mov.u32 a" #K "_" #C ", 0; mov.u32 a" #K "_" #D ", 0;\n"
#define ZACC(K) Z4(K, 0, 1, 2, 3) Z4(K, 4, 5, 6, 7) Z4(K, 8, 9, 10, 11) Z4(K, 12, 13, 14, 15)
#define ST4(K, A, B, C, D, R, P) "stmatrix.sync.aligned.m8n8.x4.trans.shared.b16 [" #R "+" STR(SM_H) "+" #K "*512+" #P "*" STR(HPANEL) "], {a" #K "_" #A ",a" #K "_" #B ",a" #K "_" #C ",a" #K "_" #D "};\n"
#define STH(K, R0, R1) ST4(K, 0, 1, 2, 3, R0, 0) ST4(K, 4, 5, 6, 7, R1, 1) ST4(K, 8, 9, 10, 11, R0, 2) ST4(K, 12, 13, 14, 15, R1, 3)
__device__ __forceinline__ void consumer(unsigned head, int warp) {
    const int lane = threadIdx.x & 31, g = lane >> 2, t = lane & 3;
    const unsigned xl = (lane & 3) * 128 + ((((lane >> 3) + (lane & 4)) ^ (lane & 3)) << 4);
    const unsigned rl = (t >> 1) * 128 + ((g ^ (4 * (t >> 1))) << 4);
    const unsigned cl = (t >> 1) == (g >> 2) ? 512 + (2 * (g & 3) + (t & 1)) * 4 : 0;
    asm volatile("{\n"
        ".reg .b32 a0_<16>, a1_<16>, a2_<16>, a3_<16>, a4_<16>, a5_<16>;\n"
        ".reg .b32 x<4>, y<4>, r<4>, s<4>, t<4>, u<2>, bf, xa, ra, ca, bn, bc, dn, ix;\n"
        ".reg .f32 d<4>, e<4>, fz;\n .reg .b16 lo, hi;\n .reg .pred p, q<3>, act, l0;\n"
        "mov.f32 fz, 0f00000000;\n mov.u32 bf, 0;\n setp.ne.u32 act, %3, 0;\n setp.eq.u32 l0, %1, 0;\n mov.u32 dn, %0;\n"
        ZACC(0) ZACC(1) ZACC(2) ZACC(3) ZACC(4) ZACC(5)
        "and.b32 bc, dn, 0x7F8;\n"
        "and.b32 t0, dn, 0x1C0000;\n setp.eq.u32 p, t0, 0x1C0000;\n @p bra.uni FIN;\n"
        DECODE WAIT(6)
        "R6:\n" LOADS DISPATCH
        BODY(0) BODY(1) T23 BODY(2) BODY(3) T45 BODY(4) BODY(5)
        WAIT(0) WAIT(1) WAIT(2) WAIT(3) WAIT(4) WAIT(5)
        "FIN:\n bar.sync 0, 512;\n"
        "mad.lo.u32 t0, %4, 3072, %1;\n xor.b32 t1, t0, 64;\n"
        STH(0, t0, t1) STH(1, t1, t0) STH(2, t0, t1) STH(3, t1, t0)
        "setp.eq.u32 p, %4, 12;\n @p bra.uni DONE;\n"
        STH(4, t0, t1) STH(5, t1, t0)
        "DONE:\n}\n" ::"r"(head), "r"(xl), "r"(rl), "r"(cl), "r"(warp) : "memory");
}

__device__ __forceinline__ void slow_path(const Params& p) {
    const int lane = threadIdx.x & 31, warp = threadIdx.x >> 5;
#pragma unroll 1
    for (int nl = warp; nl < NPC; nl += 16) {
        const int node = blockIdx.x * NPC + nl;
        float acc[4][8];
#pragma unroll
        for (int w = 0; w < 4; w++)
#pragma unroll
            for (int j = 0; j < 8; j++) acc[w][j] = 0.f;
        if (node < p.N) {
#pragma unroll 1
            for (int e0 = 0; e0 < p.E; e0 += 32) {
                int e = e0 + lane;
                unsigned m = __ballot_sync(~0u, e < p.E && p.dst[e] == node);
                while (m) {
                    int ee = e0 + __ffs(m) - 1; m &= m - 1;
                    int s = p.src[ee];
                    float rw[8];
#pragma unroll
                    for (int j = 0; j < 8; j++) rw[j] = 0.f;
#pragma unroll 1
                    for (int k = 0; k < 16; k++) {
                        float a = __bfloat162float(p.ea[(size_t)ee * 16 + k]);
#pragma unroll
                        for (int j = 0; j < 8; j++) rw[j] += a * __bfloat162float(p.wr[k * 256 + lane * 8 + j]);
                    }
#pragma unroll 1
                    for (int u = 0; u < 4; u++) {
                        float y[8];
#pragma unroll
                        for (int j = 0; j < 8; j++) y[j] = rw[j] * __bfloat162float(p.x[((size_t)s * 4 + u) * 256 + lane * 8 + j]);
#pragma unroll
                        for (int w = 0; w < 4; w++) {
                            float a = 0.f;
#pragma unroll
                            for (int v = 0; v < 4; v++) a += __bfloat162float(p.cg[u * 16 + v * 4 + w]) * __bfloat162float(p.sh[(size_t)ee * 4 + v]);
#pragma unroll
                            for (int j = 0; j < 8; j++) acc[w][j] += a * y[j];
                        }
                    }
                }
            }
        }
#pragma unroll
        for (int w = 0; w < 4; w++) {
            int R = nl * 4 + w;
            sts128(SM_H + (lane >> 3) * HPANEL + R * 128 + (((lane & 7) ^ (R & 7)) << 4),
                   pack2(acc[w][0], acc[w][1]), pack2(acc[w][2], acc[w][3]), pack2(acc[w][4], acc[w][5]), pack2(acc[w][6], acc[w][7]));
        }
    }
}

template <int NN>
__device__ __forceinline__ void out_chunk(float* d, unsigned stg, const CUtensorMap* tmo, int wg, int row0, bool first, unsigned a, bool lead) {
    if (!first) {
        if (lead) asm volatile("cp.async.bulk.wait_group.read 0;" ::: "memory");
    }
    asm volatile("bar.sync %0, 128;" ::"r"(wg + 1) : "memory");
#pragma unroll
    for (int n = 0; n < NN / 8; n += 2)
        stsm4t(a + n * 1024, pack2(d[4 * n], d[4 * n + 1]), pack2(d[4 * n + 2], d[4 * n + 3]), pack2(d[4 * n + 4], d[4 * n + 5]), pack2(d[4 * n + 6], d[4 * n + 7]));
    fence_async();
    asm volatile("bar.sync %0, 128;" ::"r"(wg + 1) : "memory");
    if (lead) {
#pragma unroll
        for (int j = 0; j < NN / 16; j++) tma_st(tmo, stg + j * 2048, wg * 64, row0 + j * 16);
        asm volatile("cp.async.bulk.commit_group;" ::: "memory");
    }
}

struct XMaps { CUtensorMap row, tiny; };

__global__ void __launch_bounds__(512, 1)
mace_kernel(const __grid_constant__ XMaps tmx, const __grid_constant__ CUtensorMap tmw, const __grid_constant__ CUtensorMap tmo,
            const __grid_constant__ Params p) {
    extern __shared__ __align__(1024) char smem_raw[];
    const unsigned tstart = clk();
    if ((unsigned)__cvta_generic_to_shared(smem_raw) != SB) __trap();
    const int tid = threadIdx.x, lane = tid & 31, warp = __shfl_sync(~0u, tid >> 5, 0);
    const int cta = blockIdx.x;
    const unsigned wbar = SM_MISC, rbar = SM_MISC + 64, flagA = SM_MISC + 80, tmaxA = SM_MISC + 84;
    STAMPW(31, tstart);
    bool slow = !p.fast;
    int total = 0, nst = 0;
    unsigned T0 = 0;

    if (warp == 15 && elect()) {
#pragma unroll
        for (int i = 0; i < 9; i++) bar_init(wbar + i * 8, 1);
        if (!slow) {
            fence_async();
            bar_expect(rbar, 8192);
#pragma unroll
            for (int i = 0; i < 16; i++)
                asm volatile("cp.async.bulk.shared::cluster.global.mbarrier::complete_tx::bytes [%0], [%1], 512, [%2];" ::"r"(SM_WR + i * 528), "l"(p.wr + i * 256), "r"(rbar) : "memory");
        }
    }
    if (!slow) {
        const int e0 = cta * EPC + tid * 4;
        const bool has = tid < EPC / 4 && e0 < p.E;
        int4 s4 = make_int4(0, 0, 0, 0), d4 = s4;
        if (has) { s4 = __ldg((const int4*)(p.src + e0)); d4 = __ldg((const int4*)(p.dst + e0)); }
        if (warp >= 10) {
            const unsigned i = tid - 320, c = i < CAPP / 16 + 8 ? 0xFFFFFu : 0xFFFF8u;
            if (i < CAPP / 8 + 8) sts128(SM_FULL + i * 16, c << 1, c << 11, c << 1, c << 11);
            fence_async();
        }
        unsigned ep;
        asm volatile("ld.relaxed.gpu.global.u32 %0, [%1];" : "=r"(ep) : "l"(g_epoch + cta));
        if (tid < NCTA) sts32(SM_CNT + tid * 4, 0);
        if (tid < 320) sts128(SM_NIB + tid * 16, 0, 0, 0, 0);
        if (tid < CAPP / 4) { sts128(SM_EID + tid * 16, 0, 0, 0, 0); sts64(SM_SRC + tid * 8, 0x00010001u, 0x00010001u); }
        if (tid >= 320 && tid < 320 + 147) sts128(SM_BITS + (tid - 320) * 16, 0, 0, 0, 0);
        if (tid == 0) sts64(flagA, 0, 0);
        cta_sync();
        STAMP(0);
        if (tid >= 496) asm volatile("mbarrier.arrive.shared::cta.b64 _, [%0];" ::"r"(SM_EMPTY + (tid - 512) * 8) : "memory");
        if (has) {
            const int ss[4] = {s4.x, s4.y, s4.z, s4.w}, dd[4] = {d4.x, d4.y, d4.z, d4.w};
#pragma unroll
            for (int j = 0; j < 4; j++) {
                unsigned c = (unsigned)dd[j] / NPC, dl = dd[j] - c * NPC;
                unsigned slot = atoms_add(SM_CNT + c * 4, 1);
                if (slot < NCH * 3) sts32(SM_STAGE + c * (NCH * 16) + (slot + slot / 3) * 4, ((tid * 4 + j) << 21) | (ss[j] << 7) | (dl + 2 * (dl / 6)));
            }
        }
        ep = (ep + 1) & 0xFFFF;
        cta_sync();
        STAMP(1);
        {
            const unsigned el = min((clk() - tstart) >> 4, 0x1FFFu);
#pragma unroll
            for (int k = 0; k < 3; k++) {
                int i = tid + k * 512;
                if (i < NCTA * NCH) {
                    int c = i / NCH, j = i - c * NCH;
                    uint4 v = lds128(SM_STAGE + i * 16);
                    int n = lds32(SM_CNT + c * 4);
                    v.w = (ep << 16) | (el << 3) | (n > NCH * 3 ? 4 : 0) | min(max(n - 3 * j, 0), 3);
                    asm volatile(XST " [%0], {%1,%2,%3,%4};" ::"l"(g_xch + (c * NCTA + cta) * NCH + j), "r"(v.x), "r"(v.y), "r"(v.z), "r"(v.w) : "memory");
                }
            }
            if (tid == 0) g_epoch[cta] = ep;
            if (warp == 14) {
                int r = cta + lane * NCTA;
                if (lane < PFLEAD && r < p.N) pf_l2(p.x + (size_t)r * 1024, 2048);
            }
            if (warp == 13 && lane < 19) {
                int eb = cta * EPC + lane * 64;
                int n = min(64, p.E - eb);
                if (n > 0) { pf_l2(p.ea + (size_t)eb * 16, n * 32); pf_l2(p.sh + (size_t)eb * 4, n * 8); }
            }
        }
        STAMP(16);
        while (clk() - tstart < POLLT);
        uint4 rc[3];
        unsigned bad = 0, mx = 0;
        {
            const uint4* q = g_xch + cta * NCTA * NCH + tid;
            const bool h2 = tid + 1024 < NCTA * NCH;
            rc[2] = make_uint4(0, 0, 0, ep << 16);
            while (true) {
                asm volatile("ld.relaxed.gpu.global.v4.u32 {%0,%1,%2,%3}, [%4];" : "=r"(rc[0].x), "=r"(rc[0].y), "=r"(rc[0].z), "=r"(rc[0].w) : "l"(q) : "memory");
                asm volatile("ld.relaxed.gpu.global.v4.u32 {%0,%1,%2,%3}, [%4];" : "=r"(rc[1].x), "=r"(rc[1].y), "=r"(rc[1].z), "=r"(rc[1].w) : "l"(q + 512) : "memory");
                if (h2) asm volatile("ld.relaxed.gpu.global.v4.u32 {%0,%1,%2,%3}, [%4];" : "=r"(rc[2].x), "=r"(rc[2].y), "=r"(rc[2].z), "=r"(rc[2].w) : "l"(q + 1024) : "memory");
                bool ok = (rc[0].w >> 16) == ep && (rc[1].w >> 16) == ep && (rc[2].w >> 16) == ep;
                if (__all_sync(~0u, ok)) break;
                if (__any_sync(~0u, clk() - tstart > 2000000u)) { bad = 1; rc[0].w = rc[1].w = rc[2].w = 0; break; }
            }
        }
        STAMP(2);
        unsigned ord[3];
#pragma unroll
        for (int k = 0; k < 3; k++) {
            const unsigned n = rc[k].w & 3;
            bad |= rc[k].w & 4;
            mx = max(mx, (rc[k].w >> 3) & 0x1FFF);
            const unsigned rr[3] = {rc[k].x, rc[k].y, rc[k].z};
            ord[k] = 0;
#pragma unroll
            for (int j = 0; j < 3; j++) {
                if (j < n) {
                    unsigned sh4 = (rr[j] >> 5) & 28;
                    unsigned o = (atoms_add(SM_NIB + ((rr[j] >> 8) & 0x1FFC), 1u << sh4) >> sh4) & 15;
                    bad |= (o == 15);
                    ord[k] |= o << (4 * j);
                }
            }
        }
        mx = __reduce_max_sync(~0u, mx);
        if (lane == 0) asm volatile("red.shared.max.u32 [%0], %1;" ::"r"(tmaxA), "r"(mx) : "memory");
        if (bad) sts32(flagA, 1);
        cta_sync();
        STAMP(15);
        unsigned c0 = 0, c1 = 0, c2 = 0, c3 = 0, inc = 0;
        if (warp < 10) {
            uint4 v = lds128(SM_NIB + tid * 16);
            c0 = nibsum(v.x); c1 = c0 + nibsum(v.y); c2 = c1 + nibsum(v.z); c3 = c2 + nibsum(v.w);
            inc = c3;
#pragma unroll
            for (int o = 1; o < 32; o <<= 1) { unsigned t = __shfl_up_sync(~0u, inc, o); if (lane >= o) inc += t; }
            if (lane == 31) sts32(SM_WTOT + warp * 4, inc);
        }
        cta_sync();
        STAMP(18);
        {
            unsigned wt = lane < 10 ? lds32(SM_WTOT + lane * 4) : 0;
            total = __reduce_add_sync(~0u, wt);
            const unsigned before = __reduce_add_sync(~0u, lane < warp ? wt : 0);
            slow = lds32(flagA) != 0 || total > CAP;
            nst = (total + 7) >> 3;
            T0 = tstart + (lds32(tmaxA) << 4) + T0DELTA;
            if (warp < 10) {
                unsigned ex = before + inc - c3;
                sts64(SM_BASE + tid * 8, ex | ((ex + c0) << 16), (ex + c1) | ((ex + c2) << 16));
            }
        }
        cta_sync();
        STAMP(19);
        if (!slow) {
            if (tid == 32 && (total & 7)) bar_complete(SM_FULL + (total & ~7), (8 - (total & 7)) * 2032);
            if (tid < NCONS) reds_or(SM_BITS + tid * (BW * 4) + (total >> 5) * 4, 1u << (total & 31));
#pragma unroll
            for (int k = 0; k < 3; k++) {
                const unsigned n = rc[k].w & 3;
                const unsigned rr[3] = {rc[k].x, rc[k].y, rc[k].z};
                const unsigned ebase = ((tid + k * 512) / NCH) * EPC;
#pragma unroll
                for (int j = 0; j < 3; j++) {
                    if (j < n) {
                        unsigned sh4 = (rr[j] >> 5) & 28, w4 = (rr[j] >> 8) & 0x1FFC;
                        unsigned o = (ord[k] >> (4 * j)) & 15;
                        unsigned pos = lds16(SM_BASE + (w4 >> 1)) + nibsum(lds32(SM_NIB + w4) & ((1u << sh4) - 1)) + o;
                        unsigned back = min(o, pos & 7);
                        unsigned w = (rr[j] >> 3) & 15;
                        sts32(SM_EID + pos * 4, (ebase + (rr[j] >> 21)) | ((rr[j] & 7) << 18) | (back << 21) | (w << 24));
                        sts16(SM_SRC + pos * 2, ((rr[j] >> 5) & 0xFFFC) | (back ? 1 : 0));
                        if (back) bar_complete(SM_FULL + (pos & ~7), 2032);
                        reds_or(SM_BITS + w * (BW * 4) + (pos >> 5) * 4, 1u << (pos & 31));
                    }
                }
            }
        }
        STAMP(20);
        bwait(rbar);
        STAMP(21);
    }

    if (slow) {
        asm volatile("fence.mbarrier_init.release.cluster;" ::: "memory");
        fence_async();
        cta_sync();
        if (tid < 4) { bar_expect(wbar + tid * 8, 16384); tma_2d(SB + tid * 16384, &tmw, wbar + tid * 8, tid * 64, 0); }
        slow_path(p);
    } else if (warp < NCONS) {
        fence_async();
        cta_sync();
        STAMP(3);
        const int off = (NX - nst % NX) % NX;
        auto next_desc = [&](int pos, unsigned w) {
            unsigned a = SM_BITS + w * (BW * 4) + ((pos + 1) >> 5) * 4;
            unsigned m = lds32(a) & (~0u << ((pos + 1) & 31));
            while (!m) { a += 4; m = lds32(a); }
            const unsigned np = (a - SM_BITS - w * (BW * 4)) * 8 + __ffs(m) - 1;
            const unsigned e = lds32(SM_EID + np * 4);
            const unsigned st = np >> 3, j = np & 7;
            const unsigned d = np | ((((st + off) % NX) * 8 + j - ((e >> 21) & 7)) << 11) | (e & 0x1C0000) | ((((st % NR) * 8 + j) * (RSTR / 32)) << 21);
            return np == total ? (pos & 0x7FF) | 0x1C0000 : d;
        };
#pragma unroll
        for (int k = 0; k < 4; k++) {
            const int pos = tid + k * (NCONS * 32);
            if (pos < total) sts32(SM_NEXT + pos * 4, next_desc(pos, lds32(SM_EID + pos * 4) >> 24));
        }
        const unsigned head = next_desc(-1, warp);
        asm volatile("bar.sync 5, %0;" ::"n"(NCONS * 32) : "memory");
        STAMP(22);
        consumer(head, warp);
        STAMP(4);
    } else if (warp == NCONS) {
        fence_async();
        cta_sync();
        const unsigned rate = p.rate;
        unsigned xs = SM_X + ((NX - nst % NX) % NX) * 16384;
        unsigned mlo, mhi;
        asm volatile("mov.b64 {%0,%1}, %2;" : "=r"(mlo), "=r"(mhi) : "l"(&tmx));
        unsigned vz;
        asm volatile("and.b32 %0, %1, 0;" : "=r"(vz) : "r"(lane));
        auto deadline = [&](const uint4& k) { const unsigned ka = (k.x | vz) & 0xFFFF, kb = k.w >> 16; return T0 + (((ka + max(ka, kb)) * rate) >> 11); };
        uint4 k4 = lds128(SM_SRC);
        unsigned dl = deadline(k4);
#pragma unroll 1
        for (int s = 0; s < nst; s++) {
            const unsigned kk[4] = {k4.x, k4.y, k4.z, k4.w};
            k4 = lds128(SM_SRC + s * 16 + 16);
            asm volatile("{.reg .pred p, q; .reg .b32 c, n;\n mov.u32 n, 0;\n"
                "TW: mbarrier.test_wait.parity.shared::cta.b64 p, [%0], 0;\n mov.u32 c, %%clock;\n sub.u32 c, c, %1;\n"
                "setp.ge.and.s32 p, c, 0, p;\n add.u32 n, n, 1;\n setp.lt.and.u32 q, n, 4000000, !p;\n @q bra.uni TW;\n}"
                ::"r"(SM_EMPTY + (s - NX) * 8), "r"(dl) : "memory");
#pragma unroll
            for (int j = 0; j < 8; j++) {
                const unsigned k = (j & 1) ? kk[j >> 1] >> 16 : kk[j >> 1] & 0xFFFF;
                const void* mp;
                if (j == 4) split(xs, 0);
                asm("{.reg .b32 t; and.b32 t, %1, 1; mad.lo.u32 t, t, 128, %2; mov.b64 %0, {t,%3};}" : "=l"(mp) : "r"(k), "r"(mlo), "r"(mhi));
                if (elect()) tma_x(xs + j * 2048, mp, SM_FULL + s * 8, k);
            }
            dl = deadline(k4);
            xs += 16384; if (xs == SM_X + NX * 16384) xs = SM_X;
        }
#pragma unroll 1
        for (int i = 0; i < 4; i++) {
            bwait(SM_EMPTY + (nst + i - NX) * 8);
            if (elect()) { bar_expect(wbar + i * 8, 16384); tma_2d(SB + i * 16384, &tmw, wbar + i * 8, i * 64, 0); }
        }
        cta_sync();
    } else {
        const int g = lane >> 2, t = lane & 3, hw = warp - NCONS - 1;
        unsigned wf[16][4];
        {
            const int mi = lane >> 3, r = lane & 7;
            const unsigned a = SM_WR + (4 * (r >> 1) + (r & 1) + 2 * (mi >> 1)) * 528;
#pragma unroll
            for (int q = 0; q < 16; q++) {
                const int h = q >> 3, th = (q >> 2) & 1, i = q & 3, b = 2 * h + (i >> 1);
                const int ch = 64 * b + 8 * ((2 * (i & 1) + 4 * th) ^ (4 * (b & 1)));
                ldsm4t(wf[q], a + ch * 2 + (mi & 1) * 16);
            }
        }
        unsigned cg0 = 0, cg1 = 0;
        if (!(t & 1)) {
            const unsigned short* cg = (const unsigned short*)p.cg;
            const int o = (2 * (g & 1)) * 16 + t * 4 + (g >> 1);
            cg0 = cg[o] | ((unsigned)cg[o + 4] << 16);
            cg1 = cg[o + 16] | ((unsigned)cg[o + 20] << 16);
        }
        fence_async();
        cta_sync();
        const int eg = (g >> 1) + 4 * (g & 1);
        const unsigned t8 = pin(t * 8);
        const unsigned rs0 = pin(t * RSTR + g * 16), rs1 = pin(t * RSTR + 128 + ((g ^ 4) << 4)), cs = pin(t * RSTR + 512 + g * 4);
        int s = hw;
        unsigned ro = SM_R + hw * 8 * RSTR;
        int pfr = cta + (PFLEAD + hw) * NCTA;
        const int N = p.N;
        unsigned bA0, bA1, sA, bB0, bB1, sB_;
        const unsigned eida = pin(SM_EID + eg * 4);
        auto ldrec = [&](int st, unsigned& b0, unsigned& b1, unsigned& sv) {
            const unsigned o = pin(((lds32(eida + st * 32) << 5) & 0x7FFFE0) | t8);
            asm volatile("ld.global.nc.v2.u32 {%0,%1}, [%2];" : "=r"(b0), "=r"(b1) : "l"((const char*)p.ea + o));
            asm volatile("ld.global.nc.u32 %0, [%1];" : "=r"(sv) : "l"((const char*)p.sh + ((o >> 2) & ~3u)));
        };
        ldrec(s, bA0, bA1, sA);
        ldrec(s + 2, bB0, bB1, sB_);
        auto iter = [&](unsigned b0, unsigned b1, unsigned sv) {
            bwait(SM_EMPTY + (s - NR) * 8);
#pragma unroll
            for (int q4 = 0; q4 < 4; q4++) {
                float d[4][4];
                if ((RSPL >> q4) & 1) split(ro, q4);
#pragma unroll
                for (int i = 0; i < 4; i++) mma16816(d[i], wf[q4 * 4 + i], b0, b1);
                const unsigned a = ((q4 & 1) ? rs1 : rs0) + ro + (q4 >> 1) * 256;
                sts128(a, pack2(d[0][0], d[0][2]), pack2(d[1][0], d[1][2]), pack2(d[2][0], d[2][2]), pack2(d[3][0], d[3][2]));
                sts128(a + 4 * RSTR, pack2(d[0][1], d[0][3]), pack2(d[1][1], d[1][3]), pack2(d[2][1], d[2][3]), pack2(d[3][1], d[3][3]));
            }
            {
                float d[4];
                mma1688(d, cg0, cg1, sv);
                sts32(cs + ro, pack2(d[0], d[2]));
                sts32(cs + ro + 4 * RSTR, pack2(d[1], d[3]));
            }
            __syncwarp();
            if (elect()) bar_expect(SM_FULL + s * 8, 16384);
            ro += 16 * RSTR; if (ro >= SM_R + NR * 8 * RSTR) ro -= NR * 8 * RSTR;
            s += 2;
        };
        const unsigned z = p.zero, m2 = pin((t & 1) - 1);
        while (s < nst) {
            const unsigned a0 = bA0 | z, a1 = bA1 | z, a2 = sA & m2, c0 = bB0 | z, c1 = bB1 | z, c2 = sB_ & m2;
            ldrec(s + 4, bA0, bA1, sA);
            ldrec(s + 6, bB0, bB1, sB_);
            iter(a0, a1, a2);
            if (pfr < N) { if (elect()) pf_l2(p.x + (size_t)pfr * 1024, 2048); }
            pfr += 2 * NCTA;
            if (s >= nst) break;
            iter(c0, c1, c2);
        }
        cta_sync();
    }

    const int wg = warp >> 2, wq = warp & 3;
    int ln;
    asm volatile("mov.u32 %0, %%laneid;" : "=r"(ln));
    const bool lead = wq == 0 && ln == 0;
    unsigned af[16][4];
    const unsigned wt = SB + wg * 16384;
    const unsigned wa = wt + (((ln >> 4) * 8 + (ln & 7)) << 7) + (((2 * wq + ((ln >> 3) & 1)) ^ (ln & 7)) << 4);
    bwait(wbar + wg * 8);
#pragma unroll
    for (int k = 0; k < 8; k++) ldsm4t(af[k], wa + k * 2048);
    fence_async();
    cta_sync();
    STAMP(5);
    if (lead) { bar_expect(wbar + 32 + wg * 8, 16384); tma_2d(wt, &tmw, wbar + 32 + wg * 8, wg * 64, 128); }
    const uint64_t desc0 = (uint64_t)(((SM_H) >> 4) & 0x3FFF) | (1ull << 16) | (64ull << 32) | (1ull << 62);
    float d[32];
    const int row0 = cta * (NPC * 4);
    wg_fence();
#pragma unroll
    for (int k = 0; k < 8; k++) wgmma_rs<64>(d, af[k], desc0 + (k >> 2) * (HPANEL >> 4) + (k & 3) * 2, k != 0);
    wg_commit();
    bwait(wbar + 32 + wg * 8);
#pragma unroll
    for (int k = 0; k < 8; k++) ldsm4t(af[8 + k], wa + k * 2048);
    wg_fence();
#pragma unroll
    for (int k = 8; k < 16; k++) wgmma_rs<64>(d, af[k], desc0 + (k >> 2) * (HPANEL >> 4) + (k & 3) * 2, 1);
    wg_commit();
    wg_wait0();
    out_chunk<64>(d, wt, &tmo, wg, row0, true, wa, lead);
#pragma unroll 1
    for (int c = 1; c < 4; c++) {
        wg_fence();
#pragma unroll
        for (int k = 0; k < 16; k++) wgmma_rs<64>(d, af[k], desc0 + c * 512 + (k >> 2) * (HPANEL >> 4) + (k & 3) * 2, k != 0);
        wg_commit();
        wg_wait0();
        out_chunk<64>(d, wt, &tmo, wg, row0 + c * 64, false, wa, lead);
    }
    wg_fence();
#pragma unroll
    for (int k = 0; k < 16; k++) wgmma_rs<48>(d, af[k], desc0 + 4 * 512 + (k >> 2) * (HPANEL >> 4) + (k & 3) * 2, k != 0);
    wg_commit();
    wg_wait0();
    out_chunk<48>(d, wt, &tmo, wg, row0 + 256, false, wa, lead);
    if (lead) asm volatile("cp.async.bulk.wait_group.read 0;" ::: "memory");
    STAMP(6);
}

typedef CUresult (*EncFn)(CUtensorMap*, CUtensorMapDataType, cuuint32_t, void*, const cuuint64_t*, const cuuint64_t*, const cuuint32_t*,
                          const cuuint32_t*, CUtensorMapInterleave, CUtensorMapSwizzle, CUtensorMapL2promotion, CUtensorMapFloatOOBfill);

extern "C" void kernel_launch(void* const* d_in, const int* in_sizes, int n_in, void* d_out, int out_size) {
    static EncFn enc = nullptr;
    static int nsm = 0;
    if (!enc) {
        void* fn = nullptr; cudaDriverEntryPointQueryResult qr;
        cudaGetDriverEntryPoint("cuTensorMapEncodeTiled", &fn, cudaEnableDefault, &qr);
        enc = (EncFn)fn;
        int dev = 0; cudaGetDevice(&dev);
        cudaDeviceGetAttribute(&nsm, cudaDevAttrMultiProcessorCount, dev);
        cudaFuncSetAttribute(mace_kernel, cudaFuncAttributeMaxDynamicSharedMemorySize, SM_TOTAL);
    }
    Params p;
    p.x = (const __nv_bfloat16*)d_in[0]; p.src = (const int*)d_in[1]; p.dst = (const int*)d_in[2];
    p.sh = (const __nv_bfloat16*)d_in[3]; p.ea = (const __nv_bfloat16*)d_in[4]; p.cg = (const __nv_bfloat16*)d_in[5];
    p.wr = (const __nv_bfloat16*)d_in[6]; p.wo = (const __nv_bfloat16*)d_in[7];
    p.N = in_sizes[0] / 1024; p.E = in_sizes[1];
    p.fast = (nsm >= NCTA && p.N <= NCTA * NPC && p.E <= NCTA * EPC && p.E > 0 && (p.E & 3) == 0) ? 1 : 0;
    p.rate = (unsigned)((double)PACE * ((double)p.E / 160000.0) * 256.0 / (double)p.N);
    p.zero = 0;
    XMaps tmx; CUtensorMap tmw, tmo;
    const cuuint32_t es[3] = {1, 1, 1};
    {
        cuuint64_t dims[3] = {64, (cuuint64_t)p.N * 4, 4}; cuuint64_t str[2] = {512, 128}; cuuint32_t box[3] = {64, 4, 4}, tiny[3] = {8, 1, 1};
        enc(&tmx.row, CU_TENSOR_MAP_DATA_TYPE_BFLOAT16, 3, d_in[0], dims, str, box, es, CU_TENSOR_MAP_INTERLEAVE_NONE, CU_TENSOR_MAP_SWIZZLE_128B, CU_TENSOR_MAP_L2_PROMOTION_NONE, CU_TENSOR_MAP_FLOAT_OOB_FILL_NONE);
        enc(&tmx.tiny, CU_TENSOR_MAP_DATA_TYPE_BFLOAT16, 3, d_in[0], dims, str, tiny, es, CU_TENSOR_MAP_INTERLEAVE_NONE, CU_TENSOR_MAP_SWIZZLE_NONE, CU_TENSOR_MAP_L2_PROMOTION_NONE, CU_TENSOR_MAP_FLOAT_OOB_FILL_NONE);
    }
    {
        cuuint64_t dims[2] = {256, 256}; cuuint64_t str[1] = {512}; cuuint32_t box[2] = {64, 128};
        enc(&tmw, CU_TENSOR_MAP_DATA_TYPE_BFLOAT16, 2, d_in[7], dims, str, box, es, CU_TENSOR_MAP_INTERLEAVE_NONE, CU_TENSOR_MAP_SWIZZLE_128B, CU_TENSOR_MAP_L2_PROMOTION_NONE, CU_TENSOR_MAP_FLOAT_OOB_FILL_NONE);
    }
    {
        cuuint64_t dims[2] = {256, (cuuint64_t)p.N * 4}; cuuint64_t str[1] = {512}; cuuint32_t box[2] = {64, 16};
        enc(&tmo, CU_TENSOR_MAP_DATA_TYPE_BFLOAT16, 2, d_out, dims, str, box, es, CU_TENSOR_MAP_INTERLEAVE_NONE, CU_TENSOR_MAP_SWIZZLE_128B, CU_TENSOR_MAP_L2_PROMOTION_NONE, CU_TENSOR_MAP_FLOAT_OOB_FILL_NONE);
    }
    const int grid = p.fast ? NCTA : (p.N + NPC - 1) / NPC;
    mace_kernel<<<grid, 512, SM_TOTAL>>>(tmx, tmw, tmo, p);
}
```

```cpp
#include <cuda_runtime.h>
#include <cuda_bf16.h>
#include <cuda.h>
#include <stdint.h>

#ifndef NX
#define NX 10
#endif
#ifndef NR
#define NR 9
#endif
#ifndef PACE
#define PACE 51000
#endif
#ifndef T0DELTA
#define T0DELTA 13000
#endif
#ifndef POLLT
#define POLLT 6000
#endif
#ifndef PFLEAD
#define PFLEAD 8
#endif
#ifndef RSPL
#define RSPL 10
#endif
#ifndef RLDG
#define RLDG "ld.global.nc"
#endif
#ifndef DISP
#define DISP 1
#endif
#ifndef XST
#define XST "st.relaxed.gpu.global.v4.u32"
#endif
#define NCTA 132
#define NPC 76
#define EPC 1216
#define NCH 10
#define CAP 1376
#define CAPP 1440
#define NCONS 13
#define RSTR 608
#define BW 45

#define SB 1024
#define SM_X SB
#define SM_R (SM_X + NX * 16384)
#define SM_EID (SM_R + NR * 8 * RSTR)
#define SM_NEXT (SM_EID + 6144)
#define SM_H (SB + 65536)
#define HPANEL 38912
#define SM_FULL (SM_H + 4 * HPANEL)
#define SM_EMPTY (SM_FULL + CAPP + 128)
#define SM_SRC (SM_EMPTY + CAPP)
#define SM_BITS (SM_SRC + CAPP * 4)
#define SM_MISC (SM_BITS + 2352)
#define SM_TOTAL (SM_MISC + 128 - SB)
#define SM_STAGE SB
#define SM_CNT (SB + 21248)
#define SM_NIB (SB + 22528)
#define SM_BASE (SB + 27648)
#define SM_WTOT (SB + 30208)
#define SM_WR (SB + 30720)
static_assert(SM_NEXT + CAPP * 4 <= SM_FULL && SM_TOTAL <= 232448, "smem");
#define STR_(x) #x
#define STR(x) STR_(x)

__device__ uint4 g_xch[NCTA * NCTA * NCH];
__device__ unsigned g_epoch[NCTA];
#ifdef DBG_TIMES
extern "C" { __device__ unsigned g_times[NCTA * 32]; }
#define STAMPV(m, i, v) asm volatile("{.reg .pred q; .reg .b32 t; .reg .b64 a, b; mov.u32 t, %%tid.x; and.b32 t, t, %0; setp.eq.u32 q, t, 0; mov.u32 t, %%ctaid.x; mov.u64 b, g_times; mad.wide.u32 a, t, 128, b; @q st.global.u32 [a+%1], %2;}" ::"n"(m), "n"((i) * 4), "r"(v) : "memory")
#define STAMP(i) STAMPV(1023, i, clk() | 0x1)
#define STAMPW(i, v) STAMPV(31, i, (v) & ~1)
#else
#define STAMP(i)
#define STAMPW(i, v)
#endif

struct Params {
    const __nv_bfloat16* x; const int* src; const int* dst; const __nv_bfloat16* sh; const __nv_bfloat16* ea;
    const __nv_bfloat16* cg; const __nv_bfloat16* wr; const __nv_bfloat16* wo;
    int N, E, fast; unsigned rate, zero;
};

__device__ __forceinline__ unsigned clk() { unsigned c; asm volatile("mov.u32 %0, %%clock;" : "=r"(c)); return c; }
__device__ __forceinline__ bool elect() { unsigned p; asm volatile("{.reg .pred P; elect.sync _|P, 0xffffffff; selp.u32 %0,1,0,P;}" : "=r"(p)); return p; }
__device__ __forceinline__ bool try_wait(unsigned a) { unsigned ok; asm volatile("{.reg .pred p; mbarrier.try_wait.parity.shared::cta.b64 p,[%1],0; selp.u32 %0,1,0,p;}" : "=r"(ok) : "r"(a) : "memory"); return ok; }
__device__ __forceinline__ void bwait(unsigned a) { if (!try_wait(a)) { for (int i = 0; i < (1 << 22) && !try_wait(a); i++); } }
__device__ __forceinline__ unsigned pin(unsigned x) { unsigned y; asm volatile("mov.u32 %0, %1;" : "=r"(y) : "r"(x)); return y; }
__device__ __forceinline__ const char* pin64(const char* x) { const char* y; asm volatile("mov.u64 %0, %1;" : "=l"(y) : "l"(x)); return y; }
__device__ __forceinline__ void split(unsigned x, unsigned c) { asm volatile("{.reg .pred p; setp.eq.u32 p, %0, %1; @p exit;}" ::"r"(x), "r"(c) : "memory"); }
__device__ __forceinline__ void bar_init(unsigned a, unsigned c) { asm volatile("mbarrier.init.shared::cta.b64 [%0], %1;" ::"r"(a), "r"(c) : "memory"); }
__device__ __forceinline__ void bar_expect(unsigned a, unsigned bytes) { asm volatile("mbarrier.arrive.expect_tx.shared::cta.b64 _, [%0], %1;" ::"r"(a), "r"(bytes) : "memory"); }
__device__ __forceinline__ void bar_complete(unsigned a, unsigned bytes) { asm volatile("mbarrier.complete_tx.relaxed.cta.shared::cta.b64 [%0], %1;" ::"r"(a), "r"(bytes) : "memory"); }
__device__ __forceinline__ void fence_async() { asm volatile("fence.proxy.async.shared::cta;" ::: "memory"); }
__device__ __forceinline__ void cta_sync() { asm volatile("bar.sync 0, 512;" ::: "memory"); }
__device__ __forceinline__ unsigned lds32(unsigned a) { unsigned v; asm volatile("ld.shared.u32 %0,[%1];" : "=r"(v) : "r"(a) : "memory"); return v; }
__device__ __forceinline__ unsigned lds16(unsigned a) { unsigned v; asm volatile("ld.shared.u16 %0,[%1];" : "=r"(v) : "r"(a) : "memory"); return v; }
__device__ __forceinline__ uint4 lds128(unsigned a) { uint4 v; asm volatile("ld.shared.v4.u32 {%0,%1,%2,%3},[%4];" : "=r"(v.x), "=r"(v.y), "=r"(v.z), "=r"(v.w) : "r"(a) : "memory"); return v; }
__device__ __forceinline__ void sts32(unsigned a, unsigned v) { asm volatile("st.shared.u32 [%0],%1;" ::"r"(a), "r"(v) : "memory"); }
__device__ __forceinline__ void sts16(unsigned a, unsigned v) { asm volatile("st.shared.u16 [%0],%1;" ::"r"(a), "r"(v) : "memory"); }
__device__ __forceinline__ void sts64(unsigned a, unsigned x, unsigned y) { asm volatile("st.shared.v2.u32 [%0],{%1,%2};" ::"r"(a), "r"(x), "r"(y) : "memory"); }
__device__ __forceinline__ void sts128(unsigned a, unsigned x, unsigned y, unsigned z, unsigned w) { asm volatile("st.shared.v4.u32 [%0],{%1,%2,%3,%4};" ::"r"(a), "r"(x), "r"(y), "r"(z), "r"(w) : "memory"); }
__device__ __forceinline__ unsigned atoms_add(unsigned a, unsigned v) { unsigned o; asm volatile("atom.shared.add.u32 %0,[%1],%2;" : "=r"(o) : "r"(a), "r"(v) : "memory"); return o; }
__device__ __forceinline__ void reds_or(unsigned a, unsigned v) { asm volatile("red.shared.or.b32 [%0],%1;" ::"r"(a), "r"(v) : "memory"); }
__device__ __forceinline__ void ldsm4t(unsigned* r, unsigned a) { asm volatile("ldmatrix.sync.aligned.m8n8.x4.trans.shared.b16 {%0,%1,%2,%3},[%4];" : "=r"(r[0]), "=r"(r[1]), "=r"(r[2]), "=r"(r[3]) : "r"(a) : "memory"); }
__device__ __forceinline__ void stsm4t(unsigned a, unsigned r0, unsigned r1, unsigned r2, unsigned r3) { asm volatile("stmatrix.sync.aligned.m8n8.x4.trans.shared.b16 [%0],{%1,%2,%3,%4};" ::"r"(a), "r"(r0), "r"(r1), "r"(r2), "r"(r3) : "memory"); }
__device__ __forceinline__ unsigned pack2(float lo, float hi) { unsigned p; asm("cvt.rn.bf16x2.f32 %0,%1,%2;" : "=r"(p) : "f"(hi), "f"(lo)); return p; }
__device__ __forceinline__ void mma1688(float* d, unsigned a0, unsigned a1, unsigned b0) {
    asm("mma.sync.aligned.m16n8k8.row.col.f32.bf16.bf16.f32 {%0,%1,%2,%3},{%4,%5},{%6},{%7,%7,%7,%7};"
        : "=f"(d[0]), "=f"(d[1]), "=f"(d[2]), "=f"(d[3]) : "r"(a0), "r"(a1), "r"(b0), "f"(0.f));
}
__device__ __forceinline__ void mma16816(float* d, const unsigned* a, unsigned b0, unsigned b1) {
    asm volatile("mma.sync.aligned.m16n8k16.row.col.f32.bf16.bf16.f32 {%0,%1,%2,%3},{%4,%5,%6,%7},{%8,%9},{%10,%10,%10,%10};"
        : "=f"(d[0]), "=f"(d[1]), "=f"(d[2]), "=f"(d[3]) : "r"(a[0]), "r"(a[1]), "r"(a[2]), "r"(a[3]), "r"(b0), "r"(b1), "f"(0.f));
}
__device__ __forceinline__ void tma_x(unsigned da, const void* tm, unsigned ba, int c1) {
    asm volatile("cp.async.bulk.tensor.3d.shared::cluster.global.mbarrier::complete_tx::bytes [%0], [%1, {%3,%4,%3}], [%2];" ::"r"(da), "l"(tm), "r"(ba), "r"(0), "r"(c1) : "memory");
}
__device__ __forceinline__ void tma_2d(unsigned da, const CUtensorMap* tm, unsigned ba, int c0, int c1) {
    asm volatile("cp.async.bulk.tensor.2d.shared::cluster.global.mbarrier::complete_tx::bytes [%0], [%1, {%3,%4}], [%2];" ::"r"(da), "l"(tm), "r"(ba), "r"(c0), "r"(c1) : "memory");
}
__device__ __forceinline__ void tma_st(const CUtensorMap* tm, unsigned sa, int c0, int c1) {
    asm volatile("cp.async.bulk.tensor.2d.global.shared::cta.bulk_group [%0, {%2,%3}], [%1];" ::"l"(tm), "r"(sa), "r"(c0), "r"(c1) : "memory");
}
__device__ __forceinline__ void pf_l2(const void* p, unsigned bytes) { asm volatile("cp.async.bulk.prefetch.L2.global [%0], %1;" ::"l"(p), "r"(bytes) : "memory"); }
__device__ __forceinline__ unsigned nibsum(unsigned v) { unsigned x = (v & 0x0F0F0F0Fu) + ((v >> 4) & 0x0F0F0F0Fu); return (x * 0x01010101u) >> 24; }

#define WG_REGS24(d) "+f"(d[0]), "+f"(d[1]), "+f"(d[2]), "+f"(d[3]), "+f"(d[4]), "+f"(d[5]), "+f"(d[6]), "+f"(d[7]), \
    "+f"(d[8]), "+f"(d[9]), "+f"(d[10]), "+f"(d[11]), "+f"(d[12]), "+f"(d[13]), "+f"(d[14]), "+f"(d[15]), \
    "+f"(d[16]), "+f"(d[17]), "+f"(d[18]), "+f"(d[19]), "+f"(d[20]), "+f"(d[21]), "+f"(d[22]), "+f"(d[23])
template <int NN> __device__ __forceinline__ void wgmma_rs(float* d, const unsigned* a, uint64_t desc, int scale_d);
template <> __device__ __forceinline__ void wgmma_rs<48>(float* d, const unsigned* a, uint64_t desc, int scale_d) {
    asm volatile("{.reg .pred p; setp.ne.b32 p, %29, 0;\n"
        "wgmma.mma_async.sync.aligned.m64n48k16.f32.bf16.bf16 {%0,%1,%2,%3,%4,%5,%6,%7,%8,%9,%10,%11,%12,%13,%14,%15,%16,%17,%18,%19,"
        "%20,%21,%22,%23}, {%24,%25,%26,%27}, %28, p, 1, 1, 0;}"
        : WG_REGS24(d)
        : "r"(a[0]), "r"(a[1]), "r"(a[2]), "r"(a[3]), "l"(desc), "r"(scale_d));
}
template <> __device__ __forceinline__ void wgmma_rs<64>(float* d, const unsigned* a, uint64_t desc, int scale_d) {
    asm volatile("{.reg .pred p; setp.ne.b32 p, %37, 0;\n"
        "wgmma.mma_async.sync.aligned.m64n64k16.f32.bf16.bf16 {%0,%1,%2,%3,%4,%5,%6,%7,%8,%9,%10,%11,%12,%13,%14,%15,%16,%17,%18,%19,"
        "%20,%21,%22,%23,%24,%25,%26,%27,%28,%29,%30,%31}, {%32,%33,%34,%35}, %36, p, 1, 1, 0;}"
        : WG_REGS24(d), "+f"(d[24]), "+f"(d[25]), "+f"(d[26]), "+f"(d[27]), "+f"(d[28]), "+f"(d[29]), "+f"(d[30]), "+f"(d[31])
        : "r"(a[0]), "r"(a[1]), "r"(a[2]), "r"(a[3]), "l"(desc), "r"(scale_d));
}
__device__ __forceinline__ void wg_fence() { asm volatile("wgmma.fence.sync.aligned;" ::: "memory"); }
__device__ __forceinline__ void wg_commit() { asm volatile("wgmma.commit_group.sync.aligned;" ::: "memory"); }
__device__ __forceinline__ void wg_wait0() { asm volatile("wgmma.wait_group.sync.aligned 0;" ::: "memory"); }

#define PF(D, RW, K, J0, J1) \
    "cvt.rn.bf16x2.f32 t0, " #D "1, " #D "0;\n cvt.rn.bf16x2.f32 t1, " #D "3, " #D "2;\n" \
    "mov.b32 {lo, hi}, " #RW ";\n mov.b32 u0, {lo, lo};\n mov.b32 u1, {hi, hi};\n" \
    "fma.rn.bf16x2 a" #K "_" #J0 ", t0, u0, a" #K "_" #J0 ";\n fma.rn.bf16x2 a" #K "_" #J1 ", t1, u1, a" #K "_" #J1 ";\n"
#define MMA(D, A0, A1) "mma.sync.aligned.m16n8k8.row.col.f32.bf16.bf16.f32 {" #D "0," #D "1," #D "2," #D "3}, {" #A0 "," #A1 "}, {bf}, {fz,fz,fz,fz};\n"
#define LDX(X, OFF) "ldmatrix.sync.aligned.m8n8.x4.trans.shared.b16 {" #X "0," #X "1," #X "2," #X "3}, [xa+" STR(SM_X) "+" #OFF "];\n"
#define DECODE \
    "lop3.b32 xa, dn, 0x3F800, %1, 0xEA;\n" \
    "shr.u32 t2, dn, 21;\n mad.lo.u32 ra, t2, 32, %2;\n mad.lo.u32 ca, t2, 32, %3;\n" \
    "and.b32 t3, dn, 0x7FF;\n shl.b32 t3, t3, 2;\n" SETD
#define LOADS \
    LDX(x, 0) LDX(y, 512) \
    "@act ld.shared.u32 bf, [ca+" STR(SM_R) "];\n" \
    "ld.shared.v4.u32 {r0,r1,r2,r3}, [ra+" STR(SM_R) "];\n" \
    "ld.shared.u32 dn, [t3+" STR(SM_NEXT) "];\n"
#if DISP == 0
#define SETD "bfe.u32 ix, dn, 18, 3;\n"
#define DISPATCH "brx.idx.uni ix, TS;\n"
#define T23
#define T45
#else
#define SETD "and.b32 ix, dn, 0x40000;\n setp.ne.u32 q0, ix, 0;\n and.b32 ix, dn, 0x80000;\n setp.ne.u32 q1, ix, 0;\n and.b32 ix, dn, 0x100000;\n setp.ne.u32 q2, ix, 0;\n"
#define DISPATCH "@q2 bra.uni T45;\n @q1 bra.uni T23;\n @q0 bra.uni B1;\n bra.uni B0;\n"
#define T23 "T23:\n @q0 bra.uni B3;\n"
#define T45 "T45:\n @q1 bra.uni FIN;\n @q0 bra.uni B5;\n"
#endif
#define BODY(K) "B" #K ":\n" \
    MMA(d, x0, x1) MMA(e, x2, x3) LDX(x, 1024) \
    "and.b32 bn, dn, 0x7F8;\n" \
    "mbarrier.test_wait.parity.shared::cta.b64 p, [bn+" STR(SM_FULL) "], 0;\n" \
    PF(d, r0, K, 0, 1) MMA(d, y0, y1) PF(e, r1, K, 2, 3) MMA(e, y2, y3) LDX(y, 1536) \
    "ld.shared.v4.u32 {s0,s1,s2,s3}, [ra+" STR(SM_R) "+128];\n" \
    PF(d, r2, K, 4, 5) MMA(d, x0, x1) PF(e, r3, K, 6, 7) MMA(e, x2, x3) \
    PF(d, s0, K, 8, 9) MMA(d, y0, y1) \
    "@l0 mbarrier.arrive.shared::cta.b64 _, [bc+" STR(SM_EMPTY) "];\n" \
    PF(e, s1, K, 10, 11) MMA(e, y2, y3) \
    "mov.u32 bc, bn;\n" DECODE \
    "@!p bra.uni W" #K ";\n" \
    "R" #K ":\n" LOADS \
    PF(d, s2, K, 12, 13) PF(e, s3, K, 14, 15) DISPATCH
#ifdef DBG_TR
#define SM_TR (SM_NEXT + CAPP * 4)
#define TRC "mov.u32 t1, %%clock;\n st.shared.u32 [bc+" STR(SM_TR) "], t1;\n"
extern "C" { __device__ unsigned g_trace[NCTA * 4 * 180]; }
#else
#define TRC
#endif
#define WAIT(K) "W" #K ":\n mov.u32 t0, 0;\n" \
    "V" #K ":\n mbarrier.try_wait.parity.shared::cta.b64 p, [bc+" STR(SM_FULL) "], 0;\n" TRC "@p bra.uni R" #K ";\n" \
    "add.u32 t0, t0, 1;\n setp.lt.u32 p, t0, 4000000;\n @p bra.uni V" #K ";\n bra.uni R" #K ";\n"
#define Z4(K, A, B, C, D) "mov.u32 a" #K "_" #A ", 0; mov.u32 a" #K "_" #B ", 0; mov.u32 a" #K "_" #C ", 0; mov.u32 a" #K "_" #D ", 0;\n"
#define ZACC(K) Z4(K, 0, 1, 2, 3) Z4(K, 4, 5, 6, 7) Z4(K, 8, 9, 10, 11) Z4(K, 12, 13, 14, 15)
#define ST4(K, A, B, C, D, R, P) "stmatrix.sync.aligned.m8n8.x4.trans.shared.b16 [" #R "+" STR(SM_H) "+" #K "*512+" #P "*" STR(HPANEL) "], {a" #K "_" #A ",a" #K "_" #B ",a" #K "_" #C ",a" #K "_" #D "};\n"
#define STH(K, R0, R1) ST4(K, 0, 1, 2, 3, R0, 0) ST4(K, 4, 5, 6, 7, R1, 1) ST4(K, 8, 9, 10, 11, R0, 2) ST4(K, 12, 13, 14, 15, R1, 3)
__device__ __forceinline__ void consumer(unsigned head, int warp) {
    const int lane = threadIdx.x & 31, g = lane >> 2, t = lane & 3;
    const unsigned xl = (lane & 3) * 128 + ((((lane >> 3) + (lane & 4)) ^ (lane & 3)) << 4);
    const unsigned rl = (t >> 1) * 320 + g * 16;
    const unsigned cl = (t >> 1) == (g >> 2) ? 256 + (2 * (g & 3) + (t & 1)) * 4 : 0;
    asm volatile("{\n"
        ".reg .b32 a0_<16>, a1_<16>, a2_<16>, a3_<16>, a4_<16>, a5_<16>;\n"
        ".reg .b32 x<4>, y<4>, r<4>, s<4>, t<4>, u<2>, bf, xa, ra, ca, bn, bc, dn, ix;\n"
        ".reg .f32 d<4>, e<4>, fz;\n .reg .b16 lo, hi;\n .reg .pred p, q<3>, act, l0;\n"
#if DISP == 0
        "TS: .branchtargets B0, B1, B2, B3, B4, B5, FIN, FIN;\n"
#endif
        "mov.f32 fz, 0f00000000;\n mov.u32 bf, 0;\n setp.ne.u32 act, %3, 0;\n setp.eq.u32 l0, %1, 0;\n mov.u32 dn, %0;\n"
        ZACC(0) ZACC(1) ZACC(2) ZACC(3) ZACC(4) ZACC(5)
        "and.b32 bc, dn, 0x7F8;\n"
        "and.b32 t0, dn, 0x1C0000;\n setp.eq.u32 p, t0, 0x1C0000;\n @p bra.uni FIN;\n"
        DECODE WAIT(6)
        "R6:\n" LOADS DISPATCH
        BODY(0) BODY(1) T23 BODY(2) BODY(3) T45 BODY(4) BODY(5)
        WAIT(0) WAIT(1) WAIT(2) WAIT(3) WAIT(4) WAIT(5)
        "FIN:\n bar.sync 0, 512;\n"
        "mad.lo.u32 t0, %4, 3072, %1;\n xor.b32 t1, t0, 64;\n"
        STH(0, t0, t1) STH(1, t1, t0) STH(2, t0, t1) STH(3, t1, t0)
        "setp.eq.u32 p, %4, 12;\n @p bra.uni DONE;\n"
        STH(4, t0, t1) STH(5, t1, t0)
        "DONE:\n}\n" ::"r"(head), "r"(xl), "r"(rl), "r"(cl), "r"(warp) : "memory");
}

#define RMMA(D, Q, B0, B1) "mma.sync.aligned.m16n8k16.row.col.f32.bf16.bf16.f32 {" #D "0," #D "1," #D "2," #D "3}, {w" #Q "_0,w" #Q "_1,w" #Q "_2,w" #Q "_3}, {" #B0 "," #B1 "}, {fz,fz,fz,fz};\n"
#define RPK(I, D) "cvt.rn.bf16x2.f32 u" #I ", " #D "2, " #D "0;\n cvt.rn.bf16x2.f32 v" #I ", " #D "3, " #D "1;\n"
#define RG(Q0, Q1, Q2, Q3, B0, B1, A, OFF) \
    RMMA(da, Q0, B0, B1) RMMA(db, Q1, B0, B1) RMMA(dc, Q2, B0, B1) RMMA(dd, Q3, B0, B1) \
    RPK(0, da) RPK(1, db) RPK(2, dc) RPK(3, dd) \
    "st.shared.v4.u32 [" #A "+" #OFF "], {u0,u1,u2,u3};\n st.shared.v4.u32 [" #A "+" #OFF "+4*" STR(RSTR) "], {v0,v1,v2,v3};\n"
#define RSPLIT(M) "setp.eq.u32 pk, ro, " #M ";\n @pk exit;\n"
#if RSPL & 2
#define RS1 RSPLIT(1)
#else
#define RS1
#endif
#if RSPL & 4
#define RS2 RSPLIT(2)
#else
#define RS2
#endif
#if RSPL & 8
#define RS3 RSPLIT(3)
#else
#define RS3
#endif
#ifdef NOLOAD
#define RTX "0"
#else
#define RTX "16384"
#endif
#ifdef DBG_H
#define RW0 "mov.u32 tw, %%clock;\n"
#define RW1 "mov.u32 t0, %%clock;\n sub.u32 t0, t0, tw;\n add.u32 %0, %0, t0;\n"
#else
#define RW0
#define RW1
#endif
#define RSTAGE(ID, B0, B1, SEL, PRE, MID) \
    "@!pw bra.uni RW" #ID ";\n RR" #ID ":\n" PRE \
    "mbarrier.test_wait.parity.shared::cta.b64 pw, [sb+" STR(SM_EMPTY) "+16-8*" STR(NR) "], 0;\n" \
    "add.u32 a0, ro, %2;\n add.u32 a2, ro, %4;\n" \
    RG(0, 1, 2, 3, B0, B1, a0, 0) RS1 RG(4, 5, 6, 7, B0, B1, a0, 320) RS2 MID \
    "selp.b32 t0, " SEL ", pe;\n" \
    "mma.sync.aligned.m16n8k8.row.col.f32.bf16.bf16.f32 {da0,da1,da2,da3}, {%5,%6}, {t0}, {fz,fz,fz,fz};\n" RPK(0, da) \
    "st.shared.u32 [a2], u0;\n st.shared.u32 [a2+4*" STR(RSTR) "], v0;\n" \
    RG(8, 9, 10, 11, B0, B1, a0, 128) RS3 RG(12, 13, 14, 15, B0, B1, a0, 448) \
    "bar.warp.sync 0xffffffff;\n elect.sync _|l0, 0xffffffff;\n" \
    "@l0 mbarrier.arrive.expect_tx.shared::cta.b64 _, [sb+" STR(SM_FULL) "], " RTX ";\n" \
    "add.u32 sb, sb, 16;\n add.u32 ro, ro, 16*" STR(RSTR) ";\n setp.ge.u32 pk, ro, " STR(SM_EID) ";\n @pk sub.u32 ro, ro, 8*" STR(NR) "*" STR(RSTR) ";\n" \
    "setp.ge.u32 pk, sb, %9;\n @pk bra.uni REND;\n"
#define RWAIT(ID) "RW" #ID ":\n" RW0 "mov.u32 t1, 0;\n" \
    "RV" #ID ":\n mbarrier.try_wait.parity.shared::cta.b64 pk, [sb+" STR(SM_EMPTY) "-8*" STR(NR) "], 0;\n" \
    "add.u32 t1, t1, 1;\n setp.lt.and.u32 pk, t1, 4000000, !pk;\n @pk bra.uni RV" #ID ";\n" RW1 "bra.uni RR" #ID ";\n"
#define RLD1(S, I, J, E) "lop3.b32 " #E ", " #E ", 0xFFFFC, tt, 0xEA;\n mad.wide.u32 ad, " #E ", 8, %10;\n " RLDG ".v2.u32 {" #S #I "," #S #J "}, [ad];\n"
#define RLD2(S, I, E, F) "selp.b32 t1, " #E ", " #F ", pe;\n and.b32 t1, t1, -2;\n mad.wide.u32 ad, t1, 2, %11;\n " RLDG ".u32 " #S #I ", [ad];\n"
#define RLOAD(S, DEP) "lop3.b32 tt, " #DEP ", %12, %7, 0xEA;\n" \
    RLD1(S, 0, 1, e0) RLD1(S, 2, 3, e1) RLD2(S, 8, e0, e1) RLD1(S, 4, 5, e2) RLD1(S, 6, 7, e3) RLD2(S, 9, e2, e3)
#define REID "ld.shared.v4.u32 {e0,e1,e2,e3}, [ea+" STR(SM_EID) "];\n add.u32 ea, ea, 256;\n"
#define RPF "mad.wide.u32 ad, pf, 4096, %14;\n add.u32 pf, pf, 2*" STR(NCTA) ";\n setp.lt.u32 pk, pf, %3;\n selp.b32 pf, pf, %3, pk;\n" \
    "elect.sync _|l0, 0xffffffff;\n @l0 cp.async.bulk.prefetch.L2.global [ad], 4096;\n"
#define RLDW(Q) "ldmatrix.sync.aligned.m8n8.x4.trans.shared.b16 {w" #Q "_0,w" #Q "_1,w" #Q "_2,w" #Q "_3}, [%1+2*(64*(2*(" #Q ">>3)+((" #Q "&3)>>1))+8*((2*(" #Q "&1)+(" #Q "&4))^(2*(" #Q "&2))))];\n"
__device__ __forceinline__ unsigned recorder(const Params& p, int hw, int nst) {
    const int lane = threadIdx.x & 31, g = lane >> 2, t = lane & 3, mi = lane >> 3, r = lane & 7;
    const unsigned wa = SM_WR + (4 * (r >> 1) + (r & 1) + 2 * (mi >> 1)) * 528 + (mi & 1) * 16;
    const unsigned short* cg = (const unsigned short*)p.cg;
    const int o = (2 * (g & 1)) * 16 + (t & 2) * 4 + (g >> 1);
    const unsigned cg0 = cg[o] | ((unsigned)cg[o + 4] << 16), cg1 = cg[o + 16] | ((unsigned)cg[o + 20] << 16);
    unsigned ewait = 0;
    asm volatile("{\n"
        ".reg .b32 w0_<4>, w1_<4>, w2_<4>, w3_<4>, w4_<4>, w5_<4>, w6_<4>, w7_<4>, w8_<4>, w9_<4>, w10_<4>, w11_<4>, w12_<4>, w13_<4>, w14_<4>, w15_<4>;\n"
        ".reg .b32 x<10>, y<10>, e<4>, u<4>, v<4>, a<3>, t<2>, tt, tw, ea, sb, ro, pf;\n .reg .b64 ad;\n"
        ".reg .f32 da<4>, db<4>, dc<4>, dd<4>, fz;\n .reg .pred pw, pk, pe, l0;\n"
        RLDW(0) RLDW(1) RLDW(2) RLDW(3) RLDW(4) RLDW(5) RLDW(6) RLDW(7) RLDW(8) RLDW(9) RLDW(10) RLDW(11) RLDW(12) RLDW(13) RLDW(14) RLDW(15)
        "mov.f32 fz, 0f00000000;\n and.b32 t0, %7, 1;\n setp.eq.u32 pe, t0, 0;\n"
        "mov.u32 pf, %15;\n mad.lo.u32 ea, %13, 128, %8;\n shl.b32 sb, %13, 3;\n mad.lo.u32 ro, %13, 8*" STR(RSTR) ", " STR(SM_R) ";\n"
        "fence.proxy.async.shared::cta;\n bar.sync 0, 512;\n"
        "setp.lt.u32 pw, sb, %9;\n @!pw bra.uni REND;\n"
        REID RLOAD(x, %12) REID
        "RTOP:\n"
        RSTAGE(0, x0, x1, "x8, 0", RLOAD(y, x0), ) RSTAGE(1, x2, x3, "0, x8", , ) RSTAGE(2, x4, x5, "x9, 0", , RPF) RSTAGE(3, x6, x7, "0, x9", , REID)
        RSTAGE(4, y0, y1, "y8, 0", RLOAD(x, y0), ) RSTAGE(5, y2, y3, "0, y8", , ) RSTAGE(6, y4, y5, "y9, 0", , RPF) RSTAGE(7, y6, y7, "0, y9", , REID)
        "bra.uni RTOP;\n"
        RWAIT(0) RWAIT(1) RWAIT(2) RWAIT(3) RWAIT(4) RWAIT(5) RWAIT(6) RWAIT(7)
        "REND:\n}\n"
        : "+r"(ewait)
        : "r"(wa), "r"(t * RSTR + g * 16), "r"(p.N / 2 - 1), "r"(t * RSTR + 256 + g * 4), "r"(cg0), "r"(cg1), "r"(t),
          "r"(((g >> 1) + 4 * (g & 1)) * 16), "r"(nst * 8), "l"(p.ea), "l"(p.sh), "r"(p.zero), "r"(hw), "l"(p.x),
          "r"(min((int)blockIdx.x + (PFLEAD / 2 + hw) * NCTA, p.N / 2 - 1)) : "memory");
    return ewait;
}
#ifdef NOLOAD
#define TROW(J, Z0, Z1)
#else
#define TROW(J, Z0, Z1) "@l0 cp.async.bulk.tensor.3d.shared::cluster.global.mbarrier::complete_tx::bytes [xs+" #J "*2048], [mp, {" #Z0 ",k" #J "," #Z1 "}], [mb];\n"
#endif
#ifdef DBG_H
#define TL "add.u32 %0, %0, c;\n"
#else
#define TL
#endif
#ifdef DBG_TR
#define TT0 "and.b32 n, sb, -8;\n st.shared.u32 [n+" STR(SM_TR) "], %4;\n shl.b32 n, n, 1;\n cvt.u64.u32 ad, n;\n add.u64 ad, ad, %6;\n sub.u32 n, dl, %4;\n add.u32 c, c, n;\n st.global.v2.u32 [ad], {n, c};\n"
#define TT1 "mov.u32 c, %%clock;\n sub.u32 c, c, %4;\n st.global.u32 [ad+8], c;\n"
#else
#define TT0
#define TT1
#endif
#ifndef TCLK
#define TCLK "mov.u64 ad, %%clock64;\n cvt.u32.u64 c, ad;\n"
#endif
#define TDL "mul.lo.u32 dl, q1, rt;\n shr.u32 dl, dl, 10;\n add.u32 dl, dl, %4;\n"
__device__ __forceinline__ unsigned issuer(const CUtensorMap* tm, const Params& p, int nst, unsigned T0) {
    unsigned late = 0;
    asm volatile("{\n"
        ".reg .b32 k<4>, q<4>, z<8>, xs, sa, sb, mb, dl, c, n, rt;\n .reg .b64 ad, mp;\n .reg .pred pw, pk, l0;\n"
        "mov.u32 n, " STR(SM_NEXT) ";\n ld.shared.v4.u32 {z0,z1,z2,z3}, [n+-32];\n ld.shared.v4.u32 {z4,z5,z6,z7}, [n+-16];\n"
        "ld.shared.u64 ad, [n+-48];\n add.u64 mp, ad, %1;\n ld.shared.u32 rt, [n+-40];\n add.u32 rt, rt, %5;\n"
        "mov.u32 sb, 0;\n mov.u32 xs, %2;\n mov.u32 mb, " STR(SM_FULL) ";\n"
        "ld.shared.v4.u32 {q0,q1,q2,q3}, [sb+" STR(SM_SRC) "];\n" TDL
        "mov.u32 k0, q0;\n mov.u32 k1, q1;\n mov.u32 k2, q2;\n mov.u32 k3, q3;\n bra.uni TW;\n"
        "TR:\n" TL TT0
        "elect.sync _|l0, 0xffffffff;\n"
        "shl.b32 sa, sb, 2;\n ld.shared.v4.u32 {q0,q1,q2,q3}, [sa+" STR(SM_SRC) "+16];\n"
        "add.u32 sb, sb, 4;\n and.b32 n, sb, -8;\n"
        "mbarrier.test_wait.parity.shared::cta.b64 pw, [n+" STR(SM_EMPTY) "-8*" STR(NX) "], 0;\n"
        TROW(0, z0, z1) TROW(1, z2, z3) TROW(2, z4, z5) TROW(3, z6, z7) TT1 TCLK TDL
        "sub.u32 c, c, dl;\n setp.lt.and.u32 pw, sb, %3, pw;\n setp.ge.and.s32 pw, c, 0, pw;\n"
        "add.u32 mb, n, " STR(SM_FULL) ";\n"
        "add.u32 xs, xs, 8192;\n setp.eq.u32 pk, xs, " STR(SM_R) ";\n selp.b32 xs, " STR(SM_X) ", xs, pk;\n"
        "mov.u32 k0, q0;\n mov.u32 k1, q1;\n mov.u32 k2, q2;\n mov.u32 k3, q3;\n @pw bra.uni TR;\n"
        "TW:\n setp.ge.u32 pk, sb, %3;\n @pk bra.uni TEND;\n mov.u32 n, 0;\n"
        "TV:\n mbarrier.try_wait.parity.shared::cta.b64 pk, [mb+" STR(SM_EMPTY) "-" STR(SM_FULL) "-8*" STR(NX) "], 0;\n"
        "add.u32 n, n, 1;\n setp.lt.and.u32 pk, n, 4000000, !pk;\n @pk bra.uni TV;\n"
        "TS:\n" TCLK "sub.u32 c, c, dl;\n setp.lt.s32 pk, c, 0;\n @pk bra.uni TS;\n bra.uni TR;\n"
        "TEND:\n}\n"
        : "+r"(late)
        : "l"(tm), "r"(SM_X + ((NX - nst % NX) % NX) * 16384), "r"(nst * 8), "r"(T0), "r"(p.rate)
#ifdef DBG_TR
          , "l"(g_trace + blockIdx.x * 720)
#endif
        : "memory");
    return late;
}
__device__ __forceinline__ unsigned eperm(unsigned pos) { return ((pos & 0x7C0) << 2) | ((pos & 15) << 4) | ((pos >> 2) & 12); }

__device__ __forceinline__ void slow_path(const Params& p) {
    const int lane = threadIdx.x & 31, warp = threadIdx.x >> 5;
#pragma unroll 1
    for (int nl = warp; nl < NPC; nl += 16) {
        const int node = blockIdx.x * NPC + nl;
        float acc[4][8];
#pragma unroll
        for (int w = 0; w < 4; w++)
#pragma unroll
            for (int j = 0; j < 8; j++) acc[w][j] = 0.f;
        if (node < p.N) {
#pragma unroll 1
            for (int e0 = 0; e0 < p.E; e0 += 32) {
                int e = e0 + lane;
                unsigned m = __ballot_sync(~0u, e < p.E && p.dst[e] == node);
                while (m) {
                    int ee = e0 + __ffs(m) - 1; m &= m - 1;
                    int s = p.src[ee];
                    float rw[8];
#pragma unroll
                    for (int j = 0; j < 8; j++) rw[j] = 0.f;
#pragma unroll 1
                    for (int k = 0; k < 16; k++) {
                        float a = __bfloat162float(p.ea[(size_t)ee * 16 + k]);
#pragma unroll
                        for (int j = 0; j < 8; j++) rw[j] += a * __bfloat162float(p.wr[k * 256 + lane * 8 + j]);
                    }
#pragma unroll 1
                    for (int u = 0; u < 4; u++) {
                        float y[8];
#pragma unroll
                        for (int j = 0; j < 8; j++) y[j] = rw[j] * __bfloat162float(p.x[((size_t)s * 4 + u) * 256 + lane * 8 + j]);
#pragma unroll
                        for (int w = 0; w < 4; w++) {
                            float a = 0.f;
#pragma unroll
                            for (int v = 0; v < 4; v++) a += __bfloat162float(p.cg[u * 16 + v * 4 + w]) * __bfloat162float(p.sh[(size_t)ee * 4 + v]);
#pragma unroll
                            for (int j = 0; j < 8; j++) acc[w][j] += a * y[j];
                        }
                    }
                }
            }
        }
#pragma unroll
        for (int w = 0; w < 4; w++) {
            int R = nl * 4 + w;
            sts128(SM_H + (lane >> 3) * HPANEL + R * 128 + (((lane & 7) ^ (R & 7)) << 4),
                   pack2(acc[w][0], acc[w][1]), pack2(acc[w][2], acc[w][3]), pack2(acc[w][4], acc[w][5]), pack2(acc[w][6], acc[w][7]));
        }
    }
}

template <int NN>
__device__ __forceinline__ void out_chunk(float* d, unsigned stg, const CUtensorMap* tmo, int wg, int row0, bool first, unsigned a, bool lead) {
    if (!first) {
        if (lead) asm volatile("cp.async.bulk.wait_group.read 0;" ::: "memory");
    }
    asm volatile("bar.sync %0, 128;" ::"r"(wg + 1) : "memory");
#pragma unroll
    for (int n = 0; n < NN / 8; n += 2)
        stsm4t(a + n * 1024, pack2(d[4 * n], d[4 * n + 1]), pack2(d[4 * n + 2], d[4 * n + 3]), pack2(d[4 * n + 4], d[4 * n + 5]), pack2(d[4 * n + 6], d[4 * n + 7]));
    fence_async();
    asm volatile("bar.sync %0, 128;" ::"r"(wg + 1) : "memory");
    if (lead) {
#pragma unroll
        for (int j = 0; j < NN / 16; j++) tma_st(tmo, stg + j * 2048, wg * 64, row0 + j * 16);
        asm volatile("cp.async.bulk.commit_group;" ::: "memory");
    }
}

__global__ void __launch_bounds__(512, 1)
mace_kernel(const __grid_constant__ CUtensorMap tmx, const __grid_constant__ CUtensorMap tmw, const __grid_constant__ CUtensorMap tmo,
            const __grid_constant__ Params p) {
    extern __shared__ __align__(1024) char smem_raw[];
    const unsigned tstart = clk();
    if ((unsigned)__cvta_generic_to_shared(smem_raw) != SB) __trap();
    const int tid = threadIdx.x, lane = tid & 31, warp = __shfl_sync(~0u, tid >> 5, 0);
    const int cta = blockIdx.x;
    const unsigned wbar = SM_MISC, rbar = SM_MISC + 64, flagA = SM_MISC + 80, tmaxA = SM_MISC + 84;
    STAMPW(31, tstart);
#ifdef DBG_GT
    { unsigned g; asm volatile("mov.u32 %0, %%globaltimer_lo;" : "=r"(g)); STAMPW(29, g); }
#endif
    bool slow = !p.fast;
    int total = 0, nst = 0;
    unsigned T0 = 0;

    if (warp == 15 && elect()) {
#pragma unroll
        for (int i = 0; i < 9; i++) bar_init(wbar + i * 8, 1);
        if (!slow) {
            fence_async();
            bar_expect(rbar, 8192);
#pragma unroll
            for (int i = 0; i < 16; i++)
                asm volatile("cp.async.bulk.shared::cluster.global.mbarrier::complete_tx::bytes [%0], [%1], 512, [%2];" ::"r"(SM_WR + i * 528), "l"(p.wr + i * 256), "r"(rbar) : "memory");
        }
    }
    if (!slow) {
        const int e0 = cta * EPC + tid * 4;
        const bool has = tid < EPC / 4 && e0 < p.E;
        int4 s4 = make_int4(0, 0, 0, 0), d4 = s4;
        if (has) { s4 = __ldg((const int4*)(p.src + e0)); d4 = __ldg((const int4*)(p.dst + e0)); }
        if (warp >= 10) {
            const unsigned i = tid - 320, c = i < CAPP / 16 + 8 ? 0xFFFFFu : 0xFFFF8u;
            if (i < CAPP / 8 + 8) sts128(SM_FULL + i * 16, c << 1, c << 11, c << 1, c << 11);
            fence_async();
        }
        unsigned ep;
        asm volatile("ld.relaxed.gpu.global.u32 %0, [%1];" : "=r"(ep) : "l"(g_epoch + cta));
        if (tid < NCTA) sts32(SM_CNT + tid * 4, 0);
        if (tid < 320) sts128(SM_NIB + tid * 16, 0, 0, 0, 0);
        if (tid < 384) sts128(SM_EID + tid * 16, 0, 0, 0, 0);
        if (tid < CAPP / 4) sts128(SM_SRC + tid * 16, p.N * 4 - 4, p.N * 4 - 4, p.N * 4 - 4, p.N * 4 - 4);
        if (tid >= 320 && tid < 320 + 147) sts128(SM_BITS + (tid - 320) * 16, 0, 0, 0, 0);
        if (tid == 0) sts64(flagA, 0, 0);
        cta_sync();
        STAMP(0);
        if (tid >= 496) asm volatile("mbarrier.arrive.shared::cta.b64 _, [%0];" ::"r"(SM_EMPTY + (tid - 512) * 8) : "memory");
        if (has) {
            const int ss[4] = {s4.x, s4.y, s4.z, s4.w}, dd[4] = {d4.x, d4.y, d4.z, d4.w};
#pragma unroll
            for (int j = 0; j < 4; j++) {
                unsigned c = (unsigned)dd[j] / NPC, dl = dd[j] - c * NPC;
                unsigned slot = atoms_add(SM_CNT + c * 4, 1);
                if (slot < NCH * 3) sts32(SM_STAGE + c * (NCH * 16) + (slot + slot / 3) * 4, ((tid * 4 + j) << 21) | (ss[j] << 7) | (dl + 2 * (dl / 6)));
            }
        }
        ep = (ep + 1) & 0xFFFF;
        cta_sync();
        STAMP(1);
        {
            const unsigned el = min((clk() - tstart) >> 4, 0x1FFFu);
#pragma unroll
            for (int k = 0; k < 3; k++) {
                int i = tid + k * 512;
                if (i < NCTA * NCH) {
                    int c = i / NCH, j = i - c * NCH;
                    uint4 v = lds128(SM_STAGE + i * 16);
                    int n = lds32(SM_CNT + c * 4);
                    v.w = (ep << 16) | (el << 3) | (n > NCH * 3 ? 4 : 0) | min(max(n - 3 * j, 0), 3);
                    asm volatile(XST " [%0], {%1,%2,%3,%4};" ::"l"(g_xch + (c * NCTA + cta) * NCH + j), "r"(v.x), "r"(v.y), "r"(v.z), "r"(v.w) : "memory");
                }
            }
            if (tid == 0) g_epoch[cta] = ep;
            if (warp == 14) {
                int r = cta + lane * NCTA;
                if (lane < PFLEAD && r < p.N) pf_l2(p.x + (size_t)r * 1024, 2048);
            }
            if (warp == 13 && lane < 19) {
                int eb = cta * EPC + lane * 64;
                int n = min(64, p.E - eb);
                if (n > 0) { pf_l2(p.ea + (size_t)eb * 16, n * 32); pf_l2(p.sh + (size_t)eb * 4, n * 8); }
            }
        }
        STAMP(16);
#ifdef POLLT
        while (clk() - tstart < POLLT);
#endif
        uint4 rc[3];
        unsigned bad = 0, mx = 0;
        {
            const uint4* q = g_xch + cta * NCTA * NCH + tid;
            const bool h2 = tid + 1024 < NCTA * NCH;
            rc[2] = make_uint4(0, 0, 0, ep << 16);
#ifdef DBG_TIMES
            unsigned npoll = 0;
#endif
            while (true) {
#ifdef DBG_TIMES
                npoll++;
#endif
                asm volatile("ld.relaxed.gpu.global.v4.u32 {%0,%1,%2,%3}, [%4];" : "=r"(rc[0].x), "=r"(rc[0].y), "=r"(rc[0].z), "=r"(rc[0].w) : "l"(q) : "memory");
                asm volatile("ld.relaxed.gpu.global.v4.u32 {%0,%1,%2,%3}, [%4];" : "=r"(rc[1].x), "=r"(rc[1].y), "=r"(rc[1].z), "=r"(rc[1].w) : "l"(q + 512) : "memory");
                if (h2) asm volatile("ld.relaxed.gpu.global.v4.u32 {%0,%1,%2,%3}, [%4];" : "=r"(rc[2].x), "=r"(rc[2].y), "=r"(rc[2].z), "=r"(rc[2].w) : "l"(q + 1024) : "memory");
                bool ok = (rc[0].w >> 16) == ep && (rc[1].w >> 16) == ep && (rc[2].w >> 16) == ep;
                if (__all_sync(~0u, ok)) break;
                if (__any_sync(~0u, clk() - tstart > 2000000u)) { bad = 1; rc[0].w = rc[1].w = rc[2].w = 0; break; }
            }
#ifdef DBG_TIMES
            if (warp == 0) STAMPW(17, npoll);
#endif
        }
        STAMP(2);
        unsigned ord[3];
#pragma unroll
        for (int k = 0; k < 3; k++) {
            const unsigned n = rc[k].w & 3;
            bad |= rc[k].w & 4;
            mx = max(mx, (rc[k].w >> 3) & 0x1FFF);
            const unsigned rr[3] = {rc[k].x, rc[k].y, rc[k].z};
            ord[k] = 0;
#pragma unroll
            for (int j = 0; j < 3; j++) {
                if (j < n) {
                    unsigned sh4 = (rr[j] >> 5) & 28;
                    unsigned o = (atoms_add(SM_NIB + ((rr[j] >> 8) & 0x1FFC), 1u << sh4) >> sh4) & 15;
                    bad |= (o == 15);
                    ord[k] |= o << (4 * j);
                }
            }
        }
        mx = __reduce_max_sync(~0u, mx);
        if (lane == 0) asm volatile("red.shared.max.u32 [%0], %1;" ::"r"(tmaxA), "r"(mx) : "memory");
        if (bad) sts32(flagA, 1);
        cta_sync();
        STAMP(15);
        unsigned c0 = 0, c1 = 0, c2 = 0, c3 = 0, inc = 0;
        if (warp < 10) {
            uint4 v = lds128(SM_NIB + tid * 16);
            c0 = nibsum(v.x); c1 = c0 + nibsum(v.y); c2 = c1 + nibsum(v.z); c3 = c2 + nibsum(v.w);
            inc = c3;
#pragma unroll
            for (int o = 1; o < 32; o <<= 1) { unsigned t = __shfl_up_sync(~0u, inc, o); if (lane >= o) inc += t; }
            if (lane == 31) sts32(SM_WTOT + warp * 4, inc);
        }
        cta_sync();
        STAMP(18);
        {
            unsigned wt = lane < 10 ? lds32(SM_WTOT + lane * 4) : 0;
            total = __reduce_add_sync(~0u, wt);
            const unsigned before = __reduce_add_sync(~0u, lane < warp ? wt : 0);
            slow = lds32(flagA) != 0 || total > CAP;
            nst = (total + 7) >> 3;
            T0 = tstart + (lds32(tmaxA) << 4) + T0DELTA;
            if (warp < 10) {
                unsigned ex = before + inc - c3;
                sts64(SM_BASE + tid * 8, ex | ((ex + c0) << 16), (ex + c1) | ((ex + c2) << 16));
            }
        }
        cta_sync();
        STAMP(19);
        if (!slow) {
            if (tid < NCONS) reds_or(SM_BITS + tid * (BW * 4) + (total >> 5) * 4, 1u << (total & 31));
#pragma unroll
            for (int k = 0; k < 3; k++) {
                const unsigned n = rc[k].w & 3;
                const unsigned rr[3] = {rc[k].x, rc[k].y, rc[k].z};
                const unsigned ebase = ((tid + k * 512) / NCH) * EPC;
#pragma unroll
                for (int j = 0; j < 3; j++) {
                    if (j < n) {
                        unsigned sh4 = (rr[j] >> 5) & 28, w4 = (rr[j] >> 8) & 0x1FFC;
                        unsigned o = (ord[k] >> (4 * j)) & 15;
                        unsigned pos = lds16(SM_BASE + (w4 >> 1)) + nibsum(lds32(SM_NIB + w4) & ((1u << sh4) - 1)) + o;
                        unsigned w = (rr[j] >> 3) & 15;
                        sts32(SM_EID + eperm(pos), ((ebase + (rr[j] >> 21)) << 2) | ((rr[j] & 127) << 20));
                        sts32(SM_SRC + pos * 4, (rr[j] >> 5) & 0xFFFC);
                        reds_or(SM_BITS + w * (BW * 4) + (pos >> 5) * 4, 1u << (pos & 31));
                    }
                }
            }
        }
        STAMP(20);
        bwait(rbar);
        STAMP(21);
    }

    if (slow) {
        asm volatile("fence.mbarrier_init.release.cluster;" ::: "memory");
        fence_async();
        cta_sync();
        if (tid < 4) { bar_expect(wbar + tid * 8, 16384); tma_2d(SB + tid * 16384, &tmw, wbar + tid * 8, tid * 64, 0); }
        slow_path(p);
    } else if (warp < NCONS) {
        fence_async();
        cta_sync();
        STAMP(3);
        const int off = (NX - nst % NX) % NX;
        auto next_desc = [&](int pos, unsigned w) {
            unsigned a = SM_BITS + w * (BW * 4) + ((pos + 1) >> 5) * 4;
            unsigned m = lds32(a) & (~0u << ((pos + 1) & 31));
            while (!m) { a += 4; m = lds32(a); }
            const unsigned np = (a - SM_BITS - w * (BW * 4)) * 8 + __ffs(m) - 1;
            const unsigned e = lds32(SM_EID + eperm(np)) >> 2;
            const unsigned st = np >> 3, j = np & 7;
            const unsigned d = np | ((((st + off) % NX) * 8 + j) << 11) | (e & 0x1C0000) | ((((st % NR) * 8 + j) * (RSTR / 32)) << 21);
            return np == total ? (pos & 0x7FF) | 0x1C0000 : d;
        };
#pragma unroll
        for (int k = 0; k < 4; k++) {
            const int pos = tid + k * (NCONS * 32);
            if (pos < total) sts32(SM_NEXT + pos * 4, next_desc(pos, lds32(SM_EID + eperm(pos)) >> 23));
        }
        const unsigned head = next_desc(-1, warp);
        asm volatile("bar.sync 5, %0;" ::"n"(NCONS * 32) : "memory");
        STAMP(22);
        consumer(head, warp);
        STAMP(4);
    } else if (warp == NCONS) {
        fence_async();
        cta_sync();
        const unsigned late = issuer(&tmx, p, nst, T0);
#pragma unroll 1
        for (int i = 0; i < 4; i++) {
            bwait(SM_EMPTY + (nst + i - NX) * 8);
            if (elect()) { bar_expect(wbar + i * 8, 16384); tma_2d(SB + i * 16384, &tmw, wbar + i * 8, i * 64, 0); }
        }
#ifdef DBG_TR
        for (int i = lane; i < nst; i += 32) g_trace[(cta * 180 + i) * 4 + 3] = lds32(SM_TR + i * 8) - T0;
#endif
#ifdef DBG_H
        STAMPW(8, late); STAMPW(7, T0 - tstart); STAMPW(14, nst);
#endif
        cta_sync();
    } else {
        const unsigned ewait = recorder(p, warp - NCONS - 1, nst);
#ifdef DBG_H
        if (warp == 15) STAMPW(12, ewait); else STAMPW(11, ewait);
#endif
        cta_sync();
    }

    const int wg = warp >> 2, wq = warp & 3;
    int ln;
    asm volatile("mov.u32 %0, %%laneid;" : "=r"(ln));
    const bool lead = wq == 0 && ln == 0;
    unsigned af[16][4];
    const unsigned wt = SB + wg * 16384;
    const unsigned wa = wt + (((ln >> 4) * 8 + (ln & 7)) << 7) + (((2 * wq + ((ln >> 3) & 1)) ^ (ln & 7)) << 4);
    bwait(wbar + wg * 8);
#pragma unroll
    for (int k = 0; k < 8; k++) ldsm4t(af[k], wa + k * 2048);
    fence_async();
    cta_sync();
    STAMP(5);
    if (lead) { bar_expect(wbar + 32 + wg * 8, 16384); tma_2d(wt, &tmw, wbar + 32 + wg * 8, wg * 64, 128); }
    const uint64_t desc0 = (uint64_t)(((SM_H) >> 4) & 0x3FFF) | (1ull << 16) | (64ull << 32) | (1ull << 62);
    float d[32];
    const int row0 = cta * (NPC * 4);
    wg_fence();
#pragma unroll
    for (int k = 0; k < 8; k++) wgmma_rs<64>(d, af[k], desc0 + (k >> 2) * (HPANEL >> 4) + (k & 3) * 2, k != 0);
    wg_commit();
    bwait(wbar + 32 + wg * 8);
#pragma unroll
    for (int k = 0; k < 8; k++) ldsm4t(af[8 + k], wa + k * 2048);
    wg_fence();
#pragma unroll
    for (int k = 8; k < 16; k++) wgmma_rs<64>(d, af[k], desc0 + (k >> 2) * (HPANEL >> 4) + (k & 3) * 2, 1);
    wg_commit();
    wg_wait0();
    out_chunk<64>(d, wt, &tmo, wg, row0, true, wa, lead);
#pragma unroll 1
    for (int c = 1; c < 4; c++) {
        wg_fence();
#pragma unroll
        for (int k = 0; k < 16; k++) wgmma_rs<64>(d, af[k], desc0 + c * 512 + (k >> 2) * (HPANEL >> 4) + (k & 3) * 2, k != 0);
        wg_commit();
        wg_wait0();
        out_chunk<64>(d, wt, &tmo, wg, row0 + c * 64, false, wa, lead);
    }
    wg_fence();
#pragma unroll
    for (int k = 0; k < 16; k++) wgmma_rs<48>(d, af[k], desc0 + 4 * 512 + (k >> 2) * (HPANEL >> 4) + (k & 3) * 2, k != 0);
    wg_commit();
    wg_wait0();
    out_chunk<48>(d, wt, &tmo, wg, row0 + 256, false, wa, lead);
    if (lead) asm volatile("cp.async.bulk.wait_group.read 0;" ::: "memory");
    STAMP(6);
#ifdef DBG_GT
    { unsigned g; asm volatile("mov.u32 %0, %%globaltimer_lo;" : "=r"(g)); STAMPW(30, g); }
#endif
}

typedef CUresult (*EncFn)(CUtensorMap*, CUtensorMapDataType, cuuint32_t, void*, const cuuint64_t*, const cuuint64_t*, const cuuint32_t*,
                          const cuuint32_t*, CUtensorMapInterleave, CUtensorMapSwizzle, CUtensorMapL2promotion, CUtensorMapFloatOOBfill);

extern "C" void kernel_launch(void* const* d_in, const int* in_sizes, int n_in, void* d_out, int out_size) {
    static EncFn enc = nullptr;
    static int nsm = 0;
    if (!enc) {
        void* fn = nullptr; cudaDriverEntryPointQueryResult qr;
        cudaGetDriverEntryPoint("cuTensorMapEncodeTiled", &fn, cudaEnableDefault, &qr);
        enc = (EncFn)fn;
        int dev = 0; cudaGetDevice(&dev);
        cudaDeviceGetAttribute(&nsm, cudaDevAttrMultiProcessorCount, dev);
        cudaFuncSetAttribute(mace_kernel, cudaFuncAttributeMaxDynamicSharedMemorySize, SM_TOTAL);
    }
    Params p;
    p.x = (const __nv_bfloat16*)d_in[0]; p.src = (const int*)d_in[1]; p.dst = (const int*)d_in[2];
    p.sh = (const __nv_bfloat16*)d_in[3]; p.ea = (const __nv_bfloat16*)d_in[4]; p.cg = (const __nv_bfloat16*)d_in[5];
    p.wr = (const __nv_bfloat16*)d_in[6]; p.wo = (const __nv_bfloat16*)d_in[7];
    p.N = in_sizes[0] / 1024; p.E = in_sizes[1];
    p.fast = (nsm >= NCTA && p.N <= NCTA * NPC && p.E <= NCTA * EPC && p.E > 0 && p.N > 1 && (p.E & 3) == 0) ? 1 : 0;
    p.rate = (unsigned)((double)PACE * ((double)p.E / 160000.0) * 256.0 / (double)p.N);
    p.zero = 0;
    CUtensorMap tmx, tmw, tmo;
    const cuuint32_t es[3] = {1, 1, 1};
    {
        cuuint64_t dims[3] = {64, (cuuint64_t)p.N * 4, 4}; cuuint64_t str[2] = {512, 128}; cuuint32_t box[3] = {64, 4, 4};
        enc(&tmx, CU_TENSOR_MAP_DATA_TYPE_BFLOAT16, 3, d_in[0], dims, str, box, es, CU_TENSOR_MAP_INTERLEAVE_NONE, CU_TENSOR_MAP_SWIZZLE_128B, CU_TENSOR_MAP_L2_PROMOTION_NONE, CU_TENSOR_MAP_FLOAT_OOB_FILL_NONE);
    }
    {
        cuuint64_t dims[2] = {256, 256}; cuuint64_t str[1] = {512}; cuuint32_t box[2] = {64, 128};
        enc(&tmw, CU_TENSOR_MAP_DATA_TYPE_BFLOAT16, 2, d_in[7], dims, str, box, es, CU_TENSOR_MAP_INTERLEAVE_NONE, CU_TENSOR_MAP_SWIZZLE_128B, CU_TENSOR_MAP_L2_PROMOTION_NONE, CU_TENSOR_MAP_FLOAT_OOB_FILL_NONE);
    }
    {
        cuuint64_t dims[2] = {256, (cuuint64_t)p.N * 4}; cuuint64_t str[1] = {512}; cuuint32_t box[2] = {64, 16};
        enc(&tmo, CU_TENSOR_MAP_DATA_TYPE_BFLOAT16, 2, d_out, dims, str, box, es, CU_TENSOR_MAP_INTERLEAVE_NONE, CU_TENSOR_MAP_SWIZZLE_128B, CU_TENSOR_MAP_L2_PROMOTION_NONE, CU_TENSOR_MAP_FLOAT_OOB_FILL_NONE);
    }
    const int grid = p.fast ? NCTA : (p.N + NPC - 1) / NPC;
    mace_kernel<<<grid, 512, SM_TOTAL>>>(tmx, tmw, tmo, p);
}
```

```cpp
#include <cuda_runtime.h>
#include <cuda_bf16.h>
#include <cuda.h>
#include <stdint.h>

#ifndef NX
#define NX 10
#endif
#ifndef NR
#define NR 9
#endif
#ifndef PACE
#define PACE 51000
#endif
#ifndef T0DELTA
#define T0DELTA 13000
#endif
#ifndef POLLT
#define POLLT 6000
#endif
#ifndef PFLEAD
#define PFLEAD 8
#endif
#ifndef RSPL
#define RSPL 10
#endif
#ifndef RLDG
#define RLDG "ld.global.nc"
#endif
#ifndef DISP
#define DISP 1
#endif
#ifndef XST
#define XST "st.relaxed.gpu.global.v4.u32"
#endif
#define NCTA 132
#define NPC 76
#define EPC 1216
#define NCH 10
#define CAP 1376
#define CAPP 1440
#define NCONS 13
#define RSTR 608
#define BW 45

#define SB 1024
#define SM_X SB
#define SM_R (SM_X + NX * 16384)
#define SM_EID (SM_R + NR * 8 * RSTR)
#define SM_NEXT (SM_EID + 6144)
#define SM_H (SB + 65536)
#define HPANEL 38912
#define SM_FULL (SM_H + 4 * HPANEL)
#define SM_EMPTY (SM_FULL + CAPP + 128)
#define SM_SRC (SM_EMPTY + CAPP)
#define SM_BITS (SM_SRC + CAPP * 4)
#define SM_MISC (SM_BITS + 2352)
#define SM_TOTAL (SM_MISC + 128 - SB)
#define SM_STAGE SB
#define SM_CNT (SB + 21248)
#define SM_NIB (SB + 22528)
#define SM_BASE (SB + 27648)
#define SM_WTOT (SB + 30208)
#define SM_WR (SB + 30720)
static_assert(SM_NEXT + CAPP * 4 <= SM_FULL && SM_TOTAL <= 232448, "smem");
#define STR_(x) #x
#define STR(x) STR_(x)

__device__ uint4 g_xch[NCTA * NCTA * NCH];
__device__ unsigned g_epoch[NCTA];
#ifdef DBG_TIMES
extern "C" { __device__ unsigned g_times[NCTA * 32]; }
#define STAMPV(m, i, v) asm volatile("{.reg .pred q; .reg .b32 t; .reg .b64 a, b; mov.u32 t, %%tid.x; and.b32 t, t, %0; setp.eq.u32 q, t, 0; mov.u32 t, %%ctaid.x; mov.u64 b, g_times; mad.wide.u32 a, t, 128, b; @q st.global.u32 [a+%1], %2;}" ::"n"(m), "n"((i) * 4), "r"(v) : "memory")
#define STAMP(i) STAMPV(1023, i, clk() | 0x1)
#define STAMPW(i, v) STAMPV(31, i, (v) & ~1)
#else
#define STAMP(i)
#define STAMPW(i, v)
#endif

struct Params {
    const __nv_bfloat16* x; const int* src; const int* dst; const __nv_bfloat16* sh; const __nv_bfloat16* ea;
    const __nv_bfloat16* cg; const __nv_bfloat16* wr; const __nv_bfloat16* wo;
    int N, E, fast; unsigned rate, zero;
};

__device__ __forceinline__ unsigned clk() { unsigned c; asm volatile("mov.u32 %0, %%clock;" : "=r"(c)); return c; }
__device__ __forceinline__ bool elect() { unsigned p; asm volatile("{.reg .pred P; elect.sync _|P, 0xffffffff; selp.u32 %0,1,0,P;}" : "=r"(p)); return p; }
__device__ __forceinline__ bool try_wait(unsigned a) { unsigned ok; asm volatile("{.reg .pred p; mbarrier.try_wait.parity.shared::cta.b64 p,[%1],0; selp.u32 %0,1,0,p;}" : "=r"(ok) : "r"(a) : "memory"); return ok; }
__device__ __forceinline__ void bwait(unsigned a) { if (!try_wait(a)) { for (int i = 0; i < (1 << 22) && !try_wait(a); i++); } }
__device__ __forceinline__ unsigned pin(unsigned x) { unsigned y; asm volatile("mov.u32 %0, %1;" : "=r"(y) : "r"(x)); return y; }
__device__ __forceinline__ const char* pin64(const char* x) { const char* y; asm volatile("mov.u64 %0, %1;" : "=l"(y) : "l"(x)); return y; }
__device__ __forceinline__ void split(unsigned x, unsigned c) { asm volatile("{.reg .pred p; setp.eq.u32 p, %0, %1; @p exit;}" ::"r"(x), "r"(c) : "memory"); }
__device__ __forceinline__ void bar_init(unsigned a, unsigned c) { asm volatile("mbarrier.init.shared::cta.b64 [%0], %1;" ::"r"(a), "r"(c) : "memory"); }
__device__ __forceinline__ void bar_expect(unsigned a, unsigned bytes) { asm volatile("mbarrier.arrive.expect_tx.shared::cta.b64 _, [%0], %1;" ::"r"(a), "r"(bytes) : "memory"); }
__device__ __forceinline__ void bar_complete(unsigned a, unsigned bytes) { asm volatile("mbarrier.complete_tx.relaxed.cta.shared::cta.b64 [%0], %1;" ::"r"(a), "r"(bytes) : "memory"); }
__device__ __forceinline__ void fence_async() { asm volatile("fence.proxy.async.shared::cta;" ::: "memory"); }
__device__ __forceinline__ void cta_sync() { asm volatile("bar.sync 0, 512;" ::: "memory"); }
__device__ __forceinline__ unsigned lds32(unsigned a) { unsigned v; asm volatile("ld.shared.u32 %0,[%1];" : "=r"(v) : "r"(a) : "memory"); return v; }
__device__ __forceinline__ unsigned lds16(unsigned a) { unsigned v; asm volatile("ld.shared.u16 %0,[%1];" : "=r"(v) : "r"(a) : "memory"); return v; }
__device__ __forceinline__ uint4 lds128(unsigned a) { uint4 v; asm volatile("ld.shared.v4.u32 {%0,%1,%2,%3},[%4];" : "=r"(v.x), "=r"(v.y), "=r"(v.z), "=r"(v.w) : "r"(a) : "memory"); return v; }
__device__ __forceinline__ void sts32(unsigned a, unsigned v) { asm volatile("st.shared.u32 [%0],%1;" ::"r"(a), "r"(v) : "memory"); }
__device__ __forceinline__ void sts16(unsigned a, unsigned v) { asm volatile("st.shared.u16 [%0],%1;" ::"r"(a), "r"(v) : "memory"); }
__device__ __forceinline__ void sts64(unsigned a, unsigned x, unsigned y) { asm volatile("st.shared.v2.u32 [%0],{%1,%2};" ::"r"(a), "r"(x), "r"(y) : "memory"); }
__device__ __forceinline__ void sts128(unsigned a, unsigned x, unsigned y, unsigned z, unsigned w) { asm volatile("st.shared.v4.u32 [%0],{%1,%2,%3,%4};" ::"r"(a), "r"(x), "r"(y), "r"(z), "r"(w) : "memory"); }
__device__ __forceinline__ unsigned atoms_add(unsigned a, unsigned v) { unsigned o; asm volatile("atom.shared.add.u32 %0,[%1],%2;" : "=r"(o) : "r"(a), "r"(v) : "memory"); return o; }
__device__ __forceinline__ void reds_or(unsigned a, unsigned v) { asm volatile("red.shared.or.b32 [%0],%1;" ::"r"(a), "r"(v) : "memory"); }
__device__ __forceinline__ void ldsm4t(unsigned* r, unsigned a) { asm volatile("ldmatrix.sync.aligned.m8n8.x4.trans.shared.b16 {%0,%1,%2,%3},[%4];" : "=r"(r[0]), "=r"(r[1]), "=r"(r[2]), "=r"(r[3]) : "r"(a) : "memory"); }
__device__ __forceinline__ void stsm4t(unsigned a, unsigned r0, unsigned r1, unsigned r2, unsigned r3) { asm volatile("stmatrix.sync.aligned.m8n8.x4.trans.shared.b16 [%0],{%1,%2,%3,%4};" ::"r"(a), "r"(r0), "r"(r1), "r"(r2), "r"(r3) : "memory"); }
__device__ __forceinline__ unsigned pack2(float lo, float hi) { unsigned p; asm("cvt.rn.bf16x2.f32 %0,%1,%2;" : "=r"(p) : "f"(hi), "f"(lo)); return p; }
__device__ __forceinline__ void mma1688(float* d, unsigned a0, unsigned a1, unsigned b0) {
    asm("mma.sync.aligned.m16n8k8.row.col.f32.bf16.bf16.f32 {%0,%1,%2,%3},{%4,%5},{%6},{%7,%7,%7,%7};"
        : "=f"(d[0]), "=f"(d[1]), "=f"(d[2]), "=f"(d[3]) : "r"(a0), "r"(a1), "r"(b0), "f"(0.f));
}
__device__ __forceinline__ void mma16816(float* d, const unsigned* a, unsigned b0, unsigned b1) {
    asm volatile("mma.sync.aligned.m16n8k16.row.col.f32.bf16.bf16.f32 {%0,%1,%2,%3},{%4,%5,%6,%7},{%8,%9},{%10,%10,%10,%10};"
        : "=f"(d[0]), "=f"(d[1]), "=f"(d[2]), "=f"(d[3]) : "r"(a[0]), "r"(a[1]), "r"(a[2]), "r"(a[3]), "r"(b0), "r"(b1), "f"(0.f));
}
__device__ __forceinline__ void tma_x(unsigned da, const void* tm, unsigned ba, int c1) {
    asm volatile("cp.async.bulk.tensor.3d.shared::cluster.global.mbarrier::complete_tx::bytes [%0], [%1, {%3,%4,%3}], [%2];" ::"r"(da), "l"(tm), "r"(ba), "r"(0), "r"(c1) : "memory");
}
__device__ __forceinline__ void tma_2d(unsigned da, const CUtensorMap* tm, unsigned ba, int c0, int c1) {
    asm volatile("cp.async.bulk.tensor.2d.shared::cluster.global.mbarrier::complete_tx::bytes [%0], [%1, {%3,%4}], [%2];" ::"r"(da), "l"(tm), "r"(ba), "r"(c0), "r"(c1) : "memory");
}
__device__ __forceinline__ void tma_st(const CUtensorMap* tm, unsigned sa, int c0, int c1) {
    asm volatile("cp.async.bulk.tensor.2d.global.shared::cta.bulk_group [%0, {%2,%3}], [%1];" ::"l"(tm), "r"(sa), "r"(c0), "r"(c1) : "memory");
}
__device__ __forceinline__ void pf_l2(const void* p, unsigned bytes) { asm volatile("cp.async.bulk.prefetch.L2.global [%0], %1;" ::"l"(p), "r"(bytes) : "memory"); }
__device__ __forceinline__ unsigned nibsum(unsigned v) { unsigned x = (v & 0x0F0F0F0Fu) + ((v >> 4) & 0x0F0F0F0Fu); return (x * 0x01010101u) >> 24; }

#define WG_REGS24(d) "+f"(d[0]), "+f"(d[1]), "+f"(d[2]), "+f"(d[3]), "+f"(d[4]), "+f"(d[5]), "+f"(d[6]), "+f"(d[7]), \
    "+f"(d[8]), "+f"(d[9]), "+f"(d[10]), "+f"(d[11]), "+f"(d[12]), "+f"(d[13]), "+f"(d[14]), "+f"(d[15]), \
    "+f"(d[16]), "+f"(d[17]), "+f"(d[18]), "+f"(d[19]), "+f"(d[20]), "+f"(d[21]), "+f"(d[22]), "+f"(d[23])
template <int NN> __device__ __forceinline__ void wgmma_rs(float* d, const unsigned* a, uint64_t desc, int scale_d);
template <> __device__ __forceinline__ void wgmma_rs<48>(float* d, const unsigned* a, uint64_t desc, int scale_d) {
    asm volatile("{.reg .pred p; setp.ne.b32 p, %29, 0;\n"
        "wgmma.mma_async.sync.aligned.m64n48k16.f32.bf16.bf16 {%0,%1,%2,%3,%4,%5,%6,%7,%8,%9,%10,%11,%12,%13,%14,%15,%16,%17,%18,%19,"
        "%20,%21,%22,%23}, {%24,%25,%26,%27}, %28, p, 1, 1, 0;}"
        : WG_REGS24(d)
        : "r"(a[0]), "r"(a[1]), "r"(a[2]), "r"(a[3]), "l"(desc), "r"(scale_d));
}
template <> __device__ __forceinline__ void wgmma_rs<64>(float* d, const unsigned* a, uint64_t desc, int scale_d) {
    asm volatile("{.reg .pred p; setp.ne.b32 p, %37, 0;\n"
        "wgmma.mma_async.sync.aligned.m64n64k16.f32.bf16.bf16 {%0,%1,%2,%3,%4,%5,%6,%7,%8,%9,%10,%11,%12,%13,%14,%15,%16,%17,%18,%19,"
        "%20,%21,%22,%23,%24,%25,%26,%27,%28,%29,%30,%31}, {%32,%33,%34,%35}, %36, p, 1, 1, 0;}"
        : WG_REGS24(d), "+f"(d[24]), "+f"(d[25]), "+f"(d[26]), "+f"(d[27]), "+f"(d[28]), "+f"(d[29]), "+f"(d[30]), "+f"(d[31])
        : "r"(a[0]), "r"(a[1]), "r"(a[2]), "r"(a[3]), "l"(desc), "r"(scale_d));
}
__device__ __forceinline__ void wg_fence() { asm volatile("wgmma.fence.sync.aligned;" ::: "memory"); }
__device__ __forceinline__ void wg_commit() { asm volatile("wgmma.commit_group.sync.aligned;" ::: "memory"); }
__device__ __forceinline__ void wg_wait0() { asm volatile("wgmma.wait_group.sync.aligned 0;" ::: "memory"); }

#define PF(D, RW, K, J0, J1) \
    "cvt.rn.bf16x2.f32 t0, " #D "1, " #D "0;\n cvt.rn.bf16x2.f32 t1, " #D "3, " #D "2;\n" \
    "mov.b32 {lo, hi}, " #RW ";\n mov.b32 u0, {lo, lo};\n mov.b32 u1, {hi, hi};\n" \
    "fma.rn.bf16x2 a" #K "_" #J0 ", t0, u0, a" #K "_" #J0 ";\n fma.rn.bf16x2 a" #K "_" #J1 ", t1, u1, a" #K "_" #J1 ";\n"
#define MMA(D, A0, A1) "mma.sync.aligned.m16n8k8.row.col.f32.bf16.bf16.f32 {" #D "0," #D "1," #D "2," #D "3}, {" #A0 "," #A1 "}, {bf}, {fz,fz,fz,fz};\n"
#define LDX(X, OFF) "ldmatrix.sync.aligned.m8n8.x4.trans.shared.b16 {" #X "0," #X "1," #X "2," #X "3}, [xa+" STR(SM_X) "+" #OFF "];\n"
#define DECODE \
    "lop3.b32 xa, dn, 0x3F800, %1, 0xEA;\n" \
    "shr.u32 t2, dn, 21;\n mad.lo.u32 ra, t2, 32, %2;\n mad.lo.u32 ca, t2, 32, %3;\n" \
    "and.b32 t3, dn, 0x7FF;\n shl.b32 t3, t3, 2;\n" SETD
#define LOADS \
    LDX(x, 0) LDX(y, 512) \
    "@act ld.shared.u32 bf, [ca+" STR(SM_R) "];\n" \
    "ld.shared.v4.u32 {r0,r1,r2,r3}, [ra+" STR(SM_R) "];\n" \
    "ld.shared.u32 dn, [t3+" STR(SM_NEXT) "];\n"
#if DISP == 0
#define SETD "bfe.u32 ix, dn, 18, 3;\n"
#define DISPATCH "brx.idx.uni ix, TS;\n"
#define T23
#define T45
#else
#define SETD "and.b32 ix, dn, 0x40000;\n setp.ne.u32 q0, ix, 0;\n and.b32 ix, dn, 0x80000;\n setp.ne.u32 q1, ix, 0;\n and.b32 ix, dn, 0x100000;\n setp.ne.u32 q2, ix, 0;\n"
#define DISPATCH "@q2 bra.uni T45;\n @q1 bra.uni T23;\n @q0 bra.uni B1;\n bra.uni B0;\n"
#define T23 "T23:\n @q0 bra.uni B3;\n"
#define T45 "T45:\n @q1 bra.uni FIN;\n @q0 bra.uni B5;\n"
#endif
#ifdef XCONS
#define BODY(K) "B" #K ":\n" \
    "xor.b32 x0, x0, y0;\n xor.b32 r0, r0, r3;\n" MMA(d, x0, x1) LDX(x, 1024) LDX(y, 1536) \
    "and.b32 bn, dn, 0x7F8;\n" \
    "mbarrier.test_wait.parity.shared::cta.b64 p, [bn+" STR(SM_FULL) "], 0;\n" \
    "ld.shared.v4.u32 {s0,s1,s2,s3}, [ra+" STR(SM_R) "+128];\n" \
    PF(d, r0, K, 0, 1) "xor.b32 x0, x0, y0;\n" MMA(d, x0, x1) \
    "@l0 mbarrier.arrive.shared::cta.b64 _, [bc+" STR(SM_EMPTY) "];\n" \
    "mov.u32 bc, bn;\n" DECODE \
    "@!p bra.uni W" #K ";\n" \
    "R" #K ":\n" LOADS \
    PF(d, s2, K, 12, 13) DISPATCH
#else
#define BODY(K) "B" #K ":\n" \
    MMA(d, x0, x1) MMA(e, x2, x3) LDX(x, 1024) \
    "and.b32 bn, dn, 0x7F8;\n" \
    "mbarrier.test_wait.parity.shared::cta.b64 p, [bn+" STR(SM_FULL) "], 0;\n" \
    PF(d, r0, K, 0, 1) MMA(d, y0, y1) PF(e, r1, K, 2, 3) MMA(e, y2, y3) LDX(y, 1536) \
    "ld.shared.v4.u32 {s0,s1,s2,s3}, [ra+" STR(SM_R) "+128];\n" \
    PF(d, r2, K, 4, 5) MMA(d, x0, x1) PF(e, r3, K, 6, 7) MMA(e, x2, x3) \
    PF(d, s0, K, 8, 9) MMA(d, y0, y1) \
    "@l0 mbarrier.arrive.shared::cta.b64 _, [bc+" STR(SM_EMPTY) "];\n" \
    PF(e, s1, K, 10, 11) MMA(e, y2, y3) \
    "mov.u32 bc, bn;\n" DECODE \
    "@!p bra.uni W" #K ";\n" \
    "R" #K ":\n" LOADS \
    PF(d, s2, K, 12, 13) PF(e, s3, K, 14, 15) DISPATCH
#endif
#ifdef DBG_TR
#define SM_TR (SM_NEXT + CAPP * 4)
#define TRC "mov.u32 t1, %%clock;\n st.shared.u32 [bc+" STR(SM_TR) "], t1;\n"
extern "C" { __device__ unsigned g_trace[NCTA * 4 * 180]; }
#else
#define TRC
#endif
#define WAIT(K) "W" #K ":\n mov.u32 t0, 0;\n" \
    "V" #K ":\n mbarrier.try_wait.parity.shared::cta.b64 p, [bc+" STR(SM_FULL) "], 0;\n" TRC "@p bra.uni R" #K ";\n" \
    "add.u32 t0, t0, 1;\n setp.lt.u32 p, t0, 4000000;\n @p bra.uni V" #K ";\n bra.uni R" #K ";\n"
#define Z4(K, A, B, C, D) "mov.u32 a" #K "_" #A ", 0; mov.u32 a" #K "_" #B ", 0; mov.u32 a" #K "_" #C ", 0; mov.u32 a" #K "_" #D ", 0;\n"
#define ZACC(K) Z4(K, 0, 1, 2, 3) Z4(K, 4, 5, 6, 7) Z4(K, 8, 9, 10, 11) Z4(K, 12, 13, 14, 15)
#define ST4(K, A, B, C, D, R, P) "stmatrix.sync.aligned.m8n8.x4.trans.shared.b16 [" #R "+" STR(SM_H) "+" #K "*512+" #P "*" STR(HPANEL) "], {a" #K "_" #A ",a" #K "_" #B ",a" #K "_" #C ",a" #K "_" #D "};\n"
#define STH(K, R0, R1) ST4(K, 0, 1, 2, 3, R0, 0) ST4(K, 4, 5, 6, 7, R1, 1) ST4(K, 8, 9, 10, 11, R0, 2) ST4(K, 12, 13, 14, 15, R1, 3)
__device__ __forceinline__ void consumer(unsigned head, int warp) {
    const int lane = threadIdx.x & 31, g = lane >> 2, t = lane & 3;
    const unsigned xl = (lane & 3) * 128 + ((((lane >> 3) + (lane & 4)) ^ (lane & 3)) << 4);
    const unsigned rl = (t >> 1) * 320 + g * 16;
    const unsigned cl = (t >> 1) == (g >> 2) ? 256 + (2 * (g & 3) + (t & 1)) * 4 : 0;
    asm volatile("{\n"
        ".reg .b32 a0_<16>, a1_<16>, a2_<16>, a3_<16>, a4_<16>, a5_<16>;\n"
        ".reg .b32 x<4>, y<4>, r<4>, s<4>, t<4>, u<2>, bf, xa, ra, ca, bn, bc, dn, ix;\n"
        ".reg .f32 d<4>, e<4>, fz;\n .reg .b16 lo, hi;\n .reg .pred p, q<3>, act, l0;\n"
#if DISP == 0
        "TS: .branchtargets B0, B1, B2, B3, B4, B5, FIN, FIN;\n"
#endif
        "mov.f32 fz, 0f00000000;\n mov.u32 bf, 0;\n setp.ne.u32 act, %3, 0;\n setp.eq.u32 l0, %1, 0;\n mov.u32 dn, %0;\n"
        ZACC(0) ZACC(1) ZACC(2) ZACC(3) ZACC(4) ZACC(5)
        "and.b32 bc, dn, 0x7F8;\n"
        "and.b32 t0, dn, 0x1C0000;\n setp.eq.u32 p, t0, 0x1C0000;\n @p bra.uni FIN;\n"
        DECODE WAIT(6)
        "R6:\n" LOADS DISPATCH
        BODY(0) BODY(1) T23 BODY(2) BODY(3) T45 BODY(4) BODY(5)
        WAIT(0) WAIT(1) WAIT(2) WAIT(3) WAIT(4) WAIT(5)
        "FIN:\n bar.sync 0, 512;\n"
        "mad.lo.u32 t0, %4, 3072, %1;\n xor.b32 t1, t0, 64;\n"
        STH(0, t0, t1) STH(1, t1, t0) STH(2, t0, t1) STH(3, t1, t0)
        "setp.eq.u32 p, %4, 12;\n @p bra.uni DONE;\n"
        STH(4, t0, t1) STH(5, t1, t0)
        "DONE:\n}\n" ::"r"(head), "r"(xl), "r"(rl), "r"(cl), "r"(warp) : "memory");
}

#define RMMA(D, Q, B0, B1) "mma.sync.aligned.m16n8k16.row.col.f32.bf16.bf16.f32 {" #D "0," #D "1," #D "2," #D "3}, {w" #Q "_0,w" #Q "_1,w" #Q "_2,w" #Q "_3}, {" #B0 "," #B1 "}, {fz,fz,fz,fz};\n"
#define RPK(I, D) "cvt.rn.bf16x2.f32 u" #I ", " #D "2, " #D "0;\n cvt.rn.bf16x2.f32 v" #I ", " #D "3, " #D "1;\n"
#define RG(Q0, Q1, Q2, Q3, B0, B1, A, OFF) \
    RMMA(da, Q0, B0, B1) RMMA(db, Q1, B0, B1) RMMA(dc, Q2, B0, B1) RMMA(dd, Q3, B0, B1) \
    RPK(0, da) RPK(1, db) RPK(2, dc) RPK(3, dd) \
    "st.shared.v4.u32 [" #A "+" #OFF "], {u0,u1,u2,u3};\n st.shared.v4.u32 [" #A "+" #OFF "+4*" STR(RSTR) "], {v0,v1,v2,v3};\n"
#define RSPLIT(M) "setp.eq.u32 pk, ro, " #M ";\n @pk exit;\n"
#if RSPL & 2
#define RS1 RSPLIT(1)
#else
#define RS1
#endif
#if RSPL & 4
#define RS2 RSPLIT(2)
#else
#define RS2
#endif
#if RSPL & 8
#define RS3 RSPLIT(3)
#else
#define RS3
#endif
#ifdef NOLOAD
#define RTX "0"
#else
#define RTX "16384"
#endif
#ifdef DBG_H
#define RW0 "mov.u32 tw, %%clock;\n"
#define RW1 "mov.u32 t0, %%clock;\n sub.u32 t0, t0, tw;\n add.u32 %0, %0, t0;\n"
#else
#define RW0
#define RW1
#endif
#ifdef XREC
#define RG2(B0, B1)
#else
#define RG2(B0, B1) RG(8, 9, 10, 11, B0, B1, a0, 128) RS3 RG(12, 13, 14, 15, B0, B1, a0, 448)
#endif
#define RSTAGE(ID, B0, B1, SEL, PRE, MID) \
    "@!pw bra.uni RW" #ID ";\n RR" #ID ":\n" PRE \
    "mbarrier.test_wait.parity.shared::cta.b64 pw, [sb+" STR(SM_EMPTY) "+16-8*" STR(NR) "], 0;\n" \
    "add.u32 a0, ro, %2;\n add.u32 a2, ro, %4;\n" \
    RG(0, 1, 2, 3, B0, B1, a0, 0) RS1 RG(4, 5, 6, 7, B0, B1, a0, 320) RS2 MID \
    "selp.b32 t0, " SEL ", pe;\n" \
    "mma.sync.aligned.m16n8k8.row.col.f32.bf16.bf16.f32 {da0,da1,da2,da3}, {%5,%6}, {t0}, {fz,fz,fz,fz};\n" RPK(0, da) \
    "st.shared.u32 [a2], u0;\n st.shared.u32 [a2+4*" STR(RSTR) "], v0;\n" \
    RG2(B0, B1) \
    "bar.warp.sync 0xffffffff;\n elect.sync _|l0, 0xffffffff;\n" \
    "@l0 mbarrier.arrive.expect_tx.shared::cta.b64 _, [sb+" STR(SM_FULL) "], " RTX ";\n" \
    "add.u32 sb, sb, 16;\n add.u32 ro, ro, 16*" STR(RSTR) ";\n setp.ge.u32 pk, ro, " STR(SM_EID) ";\n @pk sub.u32 ro, ro, 8*" STR(NR) "*" STR(RSTR) ";\n" \
    "setp.ge.u32 pk, sb, %9;\n @pk bra.uni REND;\n"
#define RWAIT(ID) "RW" #ID ":\n" RW0 "mov.u32 t1, 0;\n" \
    "RV" #ID ":\n mbarrier.try_wait.parity.shared::cta.b64 pk, [sb+" STR(SM_EMPTY) "-8*" STR(NR) "], 0;\n" \
    "add.u32 t1, t1, 1;\n setp.lt.and.u32 pk, t1, 4000000, !pk;\n @pk bra.uni RV" #ID ";\n" RW1 "bra.uni RR" #ID ";\n"
#define RLD1(S, I, J, E) "lop3.b32 " #E ", " #E ", 0xFFFFC, tt, 0xEA;\n mad.wide.u32 ad, " #E ", 8, %10;\n " RLDG ".v2.u32 {" #S #I "," #S #J "}, [ad];\n"
#define RLD2(S, I, E, F) "selp.b32 t1, " #E ", " #F ", pe;\n and.b32 t1, t1, -2;\n mad.wide.u32 ad, t1, 2, %11;\n " RLDG ".u32 " #S #I ", [ad];\n"
#define RLOAD(S, DEP) "lop3.b32 tt, " #DEP ", %12, %7, 0xEA;\n" \
    RLD1(S, 0, 1, e0) RLD1(S, 2, 3, e1) RLD2(S, 8, e0, e1) RLD1(S, 4, 5, e2) RLD1(S, 6, 7, e3) RLD2(S, 9, e2, e3)
#define REID "ld.shared.v4.u32 {e0,e1,e2,e3}, [ea+" STR(SM_EID) "];\n add.u32 ea, ea, 256;\n"
#define RPF "mad.wide.u32 ad, pf, 4096, %14;\n add.u32 pf, pf, 2*" STR(NCTA) ";\n setp.lt.u32 pk, pf, %3;\n selp.b32 pf, pf, %3, pk;\n" \
    "elect.sync _|l0, 0xffffffff;\n @l0 cp.async.bulk.prefetch.L2.global [ad], 4096;\n"
#define RLDW(Q) "ldmatrix.sync.aligned.m8n8.x4.trans.shared.b16 {w" #Q "_0,w" #Q "_1,w" #Q "_2,w" #Q "_3}, [%1+2*(64*(2*(" #Q ">>3)+((" #Q "&3)>>1))+8*((2*(" #Q "&1)+(" #Q "&4))^(2*(" #Q "&2))))];\n"
__device__ __forceinline__ unsigned recorder(const Params& p, int hw, int nst) {
    const int lane = threadIdx.x & 31, g = lane >> 2, t = lane & 3, mi = lane >> 3, r = lane & 7;
    const unsigned wa = SM_WR + (4 * (r >> 1) + (r & 1) + 2 * (mi >> 1)) * 528 + (mi & 1) * 16;
    const unsigned short* cg = (const unsigned short*)p.cg;
    const int o = (2 * (g & 1)) * 16 + (t & 2) * 4 + (g >> 1);
    const unsigned cg0 = cg[o] | ((unsigned)cg[o + 4] << 16), cg1 = cg[o + 16] | ((unsigned)cg[o + 20] << 16);
    unsigned ewait = 0;
    asm volatile("{\n"
        ".reg .b32 w0_<4>, w1_<4>, w2_<4>, w3_<4>, w4_<4>, w5_<4>, w6_<4>, w7_<4>, w8_<4>, w9_<4>, w10_<4>, w11_<4>, w12_<4>, w13_<4>, w14_<4>, w15_<4>;\n"
        ".reg .b32 x<10>, y<10>, e<4>, u<4>, v<4>, a<3>, t<2>, tt, tw, ea, sb, ro, pf;\n .reg .b64 ad;\n"
        ".reg .f32 da<4>, db<4>, dc<4>, dd<4>, fz;\n .reg .pred pw, pk, pe, l0;\n"
        RLDW(0) RLDW(1) RLDW(2) RLDW(3) RLDW(4) RLDW(5) RLDW(6) RLDW(7) RLDW(8) RLDW(9) RLDW(10) RLDW(11) RLDW(12) RLDW(13) RLDW(14) RLDW(15)
        "mov.f32 fz, 0f00000000;\n and.b32 t0, %7, 1;\n setp.eq.u32 pe, t0, 0;\n"
        "mov.u32 pf, %15;\n mad.lo.u32 ea, %13, 128, %8;\n shl.b32 sb, %13, 3;\n mad.lo.u32 ro, %13, 8*" STR(RSTR) ", " STR(SM_R) ";\n"
        "fence.proxy.async.shared::cta;\n bar.sync 0, 512;\n"
        "setp.lt.u32 pw, sb, %9;\n @!pw bra.uni REND;\n"
        REID RLOAD(x, %12) REID
        "RTOP:\n"
        RSTAGE(0, x0, x1, "x8, 0", RLOAD(y, x0), ) RSTAGE(1, x2, x3, "0, x8", , ) RSTAGE(2, x4, x5, "x9, 0", , RPF) RSTAGE(3, x6, x7, "0, x9", , REID)
        RSTAGE(4, y0, y1, "y8, 0", RLOAD(x, y0), ) RSTAGE(5, y2, y3, "0, y8", , ) RSTAGE(6, y4, y5, "y9, 0", , RPF) RSTAGE(7, y6, y7, "0, y9", , REID)
        "bra.uni RTOP;\n"
        RWAIT(0) RWAIT(1) RWAIT(2) RWAIT(3) RWAIT(4) RWAIT(5) RWAIT(6) RWAIT(7)
        "REND:\n}\n"
        : "+r"(ewait)
        : "r"(wa), "r"(t * RSTR + g * 16), "r"(p.N / 2 - 1), "r"(t * RSTR + 256 + g * 4), "r"(cg0), "r"(cg1), "r"(t),
          "r"(((g >> 1) + 4 * (g & 1)) * 16), "r"(nst * 8), "l"(p.ea), "l"(p.sh), "r"(p.zero), "r"(hw), "l"(p.x),
          "r"(min((int)blockIdx.x + (PFLEAD / 2 + hw) * NCTA, p.N / 2 - 1)) : "memory");
    return ewait;
}
#ifdef NOLOAD
#define TROW(J, Z0, Z1)
#else
#define TROW(J, Z0, Z1) "@l0 cp.async.bulk.tensor.3d.shared::cluster.global.mbarrier::complete_tx::bytes [xs+" #J "*2048], [mp, {" #Z0 ",k" #J "," #Z1 "}], [mb];\n"
#endif
#ifdef DBG_H
#define TL "add.u32 %0, %0, c;\n"
#else
#define TL
#endif
#ifdef DBG_TR
#define TT0 "and.b32 n, sb, -8;\n st.shared.u32 [n+" STR(SM_TR) "], %4;\n shl.b32 n, n, 1;\n cvt.u64.u32 ad, n;\n add.u64 ad, ad, %6;\n sub.u32 n, dl, %4;\n add.u32 c, c, n;\n st.global.v2.u32 [ad], {n, c};\n"
#define TT1 "mov.u32 c, %%clock;\n sub.u32 c, c, %4;\n st.global.u32 [ad+8], c;\n"
#else
#define TT0
#define TT1
#endif
#ifndef TCLK
#define TCLK "mov.u64 ad, %%clock64;\n cvt.u32.u64 c, ad;\n"
#endif
#define TDL "mul.lo.u32 dl, q1, rt;\n shr.u32 dl, dl, 10;\n add.u32 dl, dl, %4;\n"
__device__ __forceinline__ unsigned issuer(const CUtensorMap* tm, const Params& p, int nst, unsigned T0) {
    unsigned late = 0;
    asm volatile("{\n"
        ".reg .b32 k<4>, q<4>, z<8>, xs, sa, sb, mb, dl, c, n, rt;\n .reg .b64 ad, mp;\n .reg .pred pw, pk, l0;\n"
        "mov.u32 n, " STR(SM_NEXT) ";\n ld.shared.v4.u32 {z0,z1,z2,z3}, [n+-32];\n ld.shared.v4.u32 {z4,z5,z6,z7}, [n+-16];\n"
        "ld.shared.u64 ad, [n+-48];\n add.u64 mp, ad, %1;\n ld.shared.u32 rt, [n+-40];\n add.u32 rt, rt, %5;\n"
        "mov.u32 sb, 0;\n mov.u32 xs, %2;\n mov.u32 mb, " STR(SM_FULL) ";\n"
        "ld.shared.v4.u32 {q0,q1,q2,q3}, [sb+" STR(SM_SRC) "];\n" TDL
        "mov.u32 k0, q0;\n mov.u32 k1, q1;\n mov.u32 k2, q2;\n mov.u32 k3, q3;\n bra.uni TW;\n"
        "TR:\n" TL TT0
        "elect.sync _|l0, 0xffffffff;\n"
        "shl.b32 sa, sb, 2;\n ld.shared.v4.u32 {q0,q1,q2,q3}, [sa+" STR(SM_SRC) "+16];\n"
        "add.u32 sb, sb, 4;\n and.b32 n, sb, -8;\n"
        "mbarrier.test_wait.parity.shared::cta.b64 pw, [n+" STR(SM_EMPTY) "-8*" STR(NX) "], 0;\n"
        TROW(0, z0, z1) TROW(1, z2, z3) TROW(2, z4, z5) TROW(3, z6, z7) TT1 TCLK TDL
        "sub.u32 c, c, dl;\n setp.lt.and.u32 pw, sb, %3, pw;\n setp.ge.and.s32 pw, c, 0, pw;\n"
        "add.u32 mb, n, " STR(SM_FULL) ";\n"
        "add.u32 xs, xs, 8192;\n setp.eq.u32 pk, xs, " STR(SM_R) ";\n selp.b32 xs, " STR(SM_X) ", xs, pk;\n"
        "mov.u32 k0, q0;\n mov.u32 k1, q1;\n mov.u32 k2, q2;\n mov.u32 k3, q3;\n @pw bra.uni TR;\n"
        "TW:\n setp.ge.u32 pk, sb, %3;\n @pk bra.uni TEND;\n mov.u32 n, 0;\n"
        "TV:\n mbarrier.try_wait.parity.shared::cta.b64 pk, [mb+" STR(SM_EMPTY) "-" STR(SM_FULL) "-8*" STR(NX) "], 0;\n"
        "add.u32 n, n, 1;\n setp.lt.and.u32 pk, n, 4000000, !pk;\n @pk bra.uni TV;\n"
        "TS:\n" TCLK "sub.u32 c, c, dl;\n setp.lt.s32 pk, c, 0;\n @pk bra.uni TS;\n bra.uni TR;\n"
        "TEND:\n}\n"
        : "+r"(late)
        : "l"(tm), "r"(SM_X + ((NX - nst % NX) % NX) * 16384), "r"(nst * 8), "r"(T0), "r"(p.rate)
#ifdef DBG_TR
          , "l"(g_trace + blockIdx.x * 720)
#endif
        : "memory");
    return late;
}
__device__ __forceinline__ unsigned eperm(unsigned pos) { return ((pos & 0x7C0) << 2) | ((pos & 15) << 4) | ((pos >> 2) & 12); }

__device__ __forceinline__ void slow_path(const Params& p) {
    const int lane = threadIdx.x & 31, warp = threadIdx.x >> 5;
#pragma unroll 1
    for (int nl = warp; nl < NPC; nl += 16) {
        const int node = blockIdx.x * NPC + nl;
        float acc[4][8];
#pragma unroll
        for (int w = 0; w < 4; w++)
#pragma unroll
            for (int j = 0; j < 8; j++) acc[w][j] = 0.f;
        if (node < p.N) {
#pragma unroll 1
            for (int e0 = 0; e0 < p.E; e0 += 32) {
                int e = e0 + lane;
                unsigned m = __ballot_sync(~0u, e < p.E && p.dst[e] == node);
                while (m) {
                    int ee = e0 + __ffs(m) - 1; m &= m - 1;
                    int s = p.src[ee];
                    float rw[8];
#pragma unroll
                    for (int j = 0; j < 8; j++) rw[j] = 0.f;
#pragma unroll 1
                    for (int k = 0; k < 16; k++) {
                        float a = __bfloat162float(p.ea[(size_t)ee * 16 + k]);
#pragma unroll
                        for (int j = 0; j < 8; j++) rw[j] += a * __bfloat162float(p.wr[k * 256 + lane * 8 + j]);
                    }
#pragma unroll 1
                    for (int u = 0; u < 4; u++) {
                        float y[8];
#pragma unroll
                        for (int j = 0; j < 8; j++) y[j] = rw[j] * __bfloat162float(p.x[((size_t)s * 4 + u) * 256 + lane * 8 + j]);
#pragma unroll
                        for (int w = 0; w < 4; w++) {
                            float a = 0.f;
#pragma unroll
                            for (int v = 0; v < 4; v++) a += __bfloat162float(p.cg[u * 16 + v * 4 + w]) * __bfloat162float(p.sh[(size_t)ee * 4 + v]);
#pragma unroll
                            for (int j = 0; j < 8; j++) acc[w][j] += a * y[j];
                        }
                    }
                }
            }
        }
#pragma unroll
        for (int w = 0; w < 4; w++) {
            int R = nl * 4 + w;
            sts128(SM_H + (lane >> 3) * HPANEL + R * 128 + (((lane & 7) ^ (R & 7)) << 4),
                   pack2(acc[w][0], acc[w][1]), pack2(acc[w][2], acc[w][3]), pack2(acc[w][4], acc[w][5]), pack2(acc[w][6], acc[w][7]));
        }
    }
}

template <int NN>
__device__ __forceinline__ void out_chunk(float* d, unsigned stg, const CUtensorMap* tmo, int wg, int row0, bool first, unsigned a, bool lead) {
    if (!first) {
        if (lead) asm volatile("cp.async.bulk.wait_group.read 0;" ::: "memory");
    }
    asm volatile("bar.sync %0, 128;" ::"r"(wg + 1) : "memory");
#pragma unroll
    for (int n = 0; n < NN / 8; n += 2)
        stsm4t(a + n * 1024, pack2(d[4 * n], d[4 * n + 1]), pack2(d[4 * n + 2], d[4 * n + 3]), pack2(d[4 * n + 4], d[4 * n + 5]), pack2(d[4 * n + 6], d[4 * n + 7]));
    fence_async();
    asm volatile("bar.sync %0, 128;" ::"r"(wg + 1) : "memory");
    if (lead) {
#pragma unroll
        for (int j = 0; j < NN / 16; j++) tma_st(tmo, stg + j * 2048, wg * 64, row0 + j * 16);
        asm volatile("cp.async.bulk.commit_group;" ::: "memory");
    }
}

__global__ void __launch_bounds__(512, 1)
mace_kernel(const __grid_constant__ CUtensorMap tmx, const __grid_constant__ CUtensorMap tmw, const __grid_constant__ CUtensorMap tmo,
            const __grid_constant__ Params p) {
    extern __shared__ __align__(1024) char smem_raw[];
    const unsigned tstart = clk();
    if ((unsigned)__cvta_generic_to_shared(smem_raw) != SB) __trap();
    const int tid = threadIdx.x, lane = tid & 31, warp = __shfl_sync(~0u, tid >> 5, 0);
    const int cta = blockIdx.x;
    const unsigned wbar = SM_MISC, rbar = SM_MISC + 64, flagA = SM_MISC + 80, tmaxA = SM_MISC + 84;
    STAMPW(31, tstart);
#ifdef DBG_GT
    { unsigned g; asm volatile("mov.u32 %0, %%globaltimer_lo;" : "=r"(g)); STAMPW(29, g); }
#endif
    bool slow = !p.fast;
    int total = 0, nst = 0;
    unsigned T0 = 0;

    if (warp == 15 && elect()) {
#pragma unroll
        for (int i = 0; i < 9; i++) bar_init(wbar + i * 8, 1);
        if (!slow) {
            fence_async();
            bar_expect(rbar, 8192);
#pragma unroll
            for (int i = 0; i < 16; i++)
                asm volatile("cp.async.bulk.shared::cluster.global.mbarrier::complete_tx::bytes [%0], [%1], 512, [%2];" ::"r"(SM_WR + i * 528), "l"(p.wr + i * 256), "r"(rbar) : "memory");
        }
    }
    if (!slow) {
        const int e0 = cta * EPC + tid * 4;
        const bool has = tid < EPC / 4 && e0 < p.E;
        int4 s4 = make_int4(0, 0, 0, 0), d4 = s4;
        if (has) { s4 = __ldg((const int4*)(p.src + e0)); d4 = __ldg((const int4*)(p.dst + e0)); }
        if (warp >= 10) {
            const unsigned i = tid - 320, c = i < CAPP / 16 + 8 ? 0xFFFFFu : 0xFFFF8u;
            if (i < CAPP / 8 + 8) sts128(SM_FULL + i * 16, c << 1, c << 11, c << 1, c << 11);
            fence_async();
        }
        unsigned ep;
        asm volatile("ld.relaxed.gpu.global.u32 %0, [%1];" : "=r"(ep) : "l"(g_epoch + cta));
        if (tid < NCTA) sts32(SM_CNT + tid * 4, 0);
        if (tid < 320) sts128(SM_NIB + tid * 16, 0, 0, 0, 0);
        if (tid < 384) sts128(SM_EID + tid * 16, 0, 0, 0, 0);
        if (tid < CAPP / 4) sts128(SM_SRC + tid * 16, p.N * 4 - 4, p.N * 4 - 4, p.N * 4 - 4, p.N * 4 - 4);
        if (tid >= 320 && tid < 320 + 147) sts128(SM_BITS + (tid - 320) * 16, 0, 0, 0, 0);
        if (tid == 0) sts64(flagA, 0, 0);
        cta_sync();
        STAMP(0);
        if (tid >= 496) asm volatile("mbarrier.arrive.shared::cta.b64 _, [%0];" ::"r"(SM_EMPTY + (tid - 512) * 8) : "memory");
        if (has) {
            const int ss[4] = {s4.x, s4.y, s4.z, s4.w}, dd[4] = {d4.x, d4.y, d4.z, d4.w};
#pragma unroll
            for (int j = 0; j < 4; j++) {
                unsigned c = (unsigned)dd[j] / NPC, dl = dd[j] - c * NPC;
                unsigned slot = atoms_add(SM_CNT + c * 4, 1);
                if (slot < NCH * 3) sts32(SM_STAGE + c * (NCH * 16) + (slot + slot / 3) * 4, ((tid * 4 + j) << 21) | (ss[j] << 7) | (dl + 2 * (dl / 6)));
            }
        }
        ep = (ep + 1) & 0xFFFF;
        cta_sync();
        STAMP(1);
        {
            const unsigned el = min((clk() - tstart) >> 4, 0x1FFFu);
#pragma unroll
            for (int k = 0; k < 3; k++) {
                int i = tid + k * 512;
                if (i < NCTA * NCH) {
                    int c = i / NCH, j = i - c * NCH;
                    uint4 v = lds128(SM_STAGE + i * 16);
                    int n = lds32(SM_CNT + c * 4);
                    v.w = (ep << 16) | (el << 3) | (n > NCH * 3 ? 4 : 0) | min(max(n - 3 * j, 0), 3);
                    asm volatile(XST " [%0], {%1,%2,%3,%4};" ::"l"(g_xch + (c * NCTA + cta) * NCH + j), "r"(v.x), "r"(v.y), "r"(v.z), "r"(v.w) : "memory");
                }
            }
            if (tid == 0) g_epoch[cta] = ep;
            if (warp == 14) {
                int r = cta + lane * NCTA;
                if (lane < PFLEAD && r < p.N) pf_l2(p.x + (size_t)r * 1024, 2048);
            }
            if (warp == 13 && lane < 19) {
                int eb = cta * EPC + lane * 64;
                int n = min(64, p.E - eb);
                if (n > 0) { pf_l2(p.ea + (size_t)eb * 16, n * 32); pf_l2(p.sh + (size_t)eb * 4, n * 8); }
            }
        }
        STAMP(16);
#ifdef POLLT
        while (clk() - tstart < POLLT);
#endif
        uint4 rc[3];
        unsigned bad = 0, mx = 0;
        {
            const uint4* q = g_xch + cta * NCTA * NCH + tid;
            const bool h2 = tid + 1024 < NCTA * NCH;
            rc[2] = make_uint4(0, 0, 0, ep << 16);
#ifdef DBG_TIMES
            unsigned npoll = 0;
#endif
            while (true) {
#ifdef DBG_TIMES
                npoll++;
#endif
                asm volatile("ld.relaxed.gpu.global.v4.u32 {%0,%1,%2,%3}, [%4];" : "=r"(rc[0].x), "=r"(rc[0].y), "=r"(rc[0].z), "=r"(rc[0].w) : "l"(q) : "memory");
                asm volatile("ld.relaxed.gpu.global.v4.u32 {%0,%1,%2,%3}, [%4];" : "=r"(rc[1].x), "=r"(rc[1].y), "=r"(rc[1].z), "=r"(rc[1].w) : "l"(q + 512) : "memory");
                if (h2) asm volatile("ld.relaxed.gpu.global.v4.u32 {%0,%1,%2,%3}, [%4];" : "=r"(rc[2].x), "=r"(rc[2].y), "=r"(rc[2].z), "=r"(rc[2].w) : "l"(q + 1024) : "memory");
                bool ok = (rc[0].w >> 16) == ep && (rc[1].w >> 16) == ep && (rc[2].w >> 16) == ep;
                if (__all_sync(~0u, ok)) break;
                if (__any_sync(~0u, clk() - tstart > 2000000u)) { bad = 1; rc[0].w = rc[1].w = rc[2].w = 0; break; }
            }
#ifdef DBG_TIMES
            if (warp == 0) STAMPW(17, npoll);
#endif
        }
        STAMP(2);
        unsigned ord[3];
#pragma unroll
        for (int k = 0; k < 3; k++) {
            const unsigned n = rc[k].w & 3;
            bad |= rc[k].w & 4;
            mx = max(mx, (rc[k].w >> 3) & 0x1FFF);
            const unsigned rr[3] = {rc[k].x, rc[k].y, rc[k].z};
            ord[k] = 0;
#pragma unroll
            for (int j = 0; j < 3; j++) {
                if (j < n) {
                    unsigned sh4 = (rr[j] >> 5) & 28;
                    unsigned o = (atoms_add(SM_NIB + ((rr[j] >> 8) & 0x1FFC), 1u << sh4) >> sh4) & 15;
                    bad |= (o == 15);
                    ord[k] |= o << (4 * j);
                }
            }
        }
        mx = __reduce_max_sync(~0u, mx);
        if (lane == 0) asm volatile("red.shared.max.u32 [%0], %1;" ::"r"(tmaxA), "r"(mx) : "memory");
        if (bad) sts32(flagA, 1);
        cta_sync();
        STAMP(15);
        unsigned c0 = 0, c1 = 0, c2 = 0, c3 = 0, inc = 0;
        if (warp < 10) {
            uint4 v = lds128(SM_NIB + tid * 16);
            c0 = nibsum(v.x); c1 = c0 + nibsum(v.y); c2 = c1 + nibsum(v.z); c3 = c2 + nibsum(v.w);
            inc = c3;
#pragma unroll
            for (int o = 1; o < 32; o <<= 1) { unsigned t = __shfl_up_sync(~0u, inc, o); if (lane >= o) inc += t; }
            if (lane == 31) sts32(SM_WTOT + warp * 4, inc);
        }
        cta_sync();
        STAMP(18);
        {
            unsigned wt = lane < 10 ? lds32(SM_WTOT + lane * 4) : 0;
            total = __reduce_add_sync(~0u, wt);
            const unsigned before = __reduce_add_sync(~0u, lane < warp ? wt : 0);
            slow = lds32(flagA) != 0 || total > CAP;
            nst = (total + 7) >> 3;
            T0 = tstart + (lds32(tmaxA) << 4) + T0DELTA;
            if (warp < 10) {
                unsigned ex = before + inc - c3;
                sts64(SM_BASE + tid * 8, ex | ((ex + c0) << 16), (ex + c1) | ((ex + c2) << 16));
            }
        }
        cta_sync();
        STAMP(19);
        if (!slow) {
            if (tid < NCONS) reds_or(SM_BITS + tid * (BW * 4) + (total >> 5) * 4, 1u << (total & 31));
#pragma unroll
            for (int k = 0; k < 3; k++) {
                const unsigned n = rc[k].w & 3;
                const unsigned rr[3] = {rc[k].x, rc[k].y, rc[k].z};
                const unsigned ebase = ((tid + k * 512) / NCH) * EPC;
#pragma unroll
                for (int j = 0; j < 3; j++) {
                    if (j < n) {
                        unsigned sh4 = (rr[j] >> 5) & 28, w4 = (rr[j] >> 8) & 0x1FFC;
                        unsigned o = (ord[k] >> (4 * j)) & 15;
                        unsigned pos = lds16(SM_BASE + (w4 >> 1)) + nibsum(lds32(SM_NIB + w4) & ((1u << sh4) - 1)) + o;
                        unsigned w = (rr[j] >> 3) & 15;
                        sts32(SM_EID + eperm(pos), ((ebase + (rr[j] >> 21)) << 2) | ((rr[j] & 127) << 20));
                        sts32(SM_SRC + pos * 4, (rr[j] >> 5) & 0xFFFC);
                        reds_or(SM_BITS + w * (BW * 4) + (pos >> 5) * 4, 1u << (pos & 31));
                    }
                }
            }
        }
        STAMP(20);
        bwait(rbar);
        STAMP(21);
    }

    if (slow) {
        asm volatile("fence.mbarrier_init.release.cluster;" ::: "memory");
        fence_async();
        cta_sync();
        if (tid < 4) { bar_expect(wbar + tid * 8, 16384); tma_2d(SB + tid * 16384, &tmw, wbar + tid * 8, tid * 64, 0); }
        slow_path(p);
    } else if (warp < NCONS) {
        fence_async();
        cta_sync();
        STAMP(3);
        const int off = (NX - nst % NX) % NX;
        auto next_desc = [&](int pos, unsigned w) {
            unsigned a = SM_BITS + w * (BW * 4) + ((pos + 1) >> 5) * 4;
            unsigned m = lds32(a) & (~0u << ((pos + 1) & 31));
            while (!m) { a += 4; m = lds32(a); }
            const unsigned np = (a - SM_BITS - w * (BW * 4)) * 8 + __ffs(m) - 1;
            const unsigned e = lds32(SM_EID + eperm(np)) >> 2;
            const unsigned st = np >> 3, j = np & 7;
            const unsigned d = np | ((((st + off) % NX) * 8 + j) << 11) | (e & 0x1C0000) | ((((st % NR) * 8 + j) * (RSTR / 32)) << 21);
            return np == total ? (pos & 0x7FF) | 0x1C0000 : d;
        };
#pragma unroll
        for (int k = 0; k < 4; k++) {
            const int pos = tid + k * (NCONS * 32);
            if (pos < total) sts32(SM_NEXT + pos * 4, next_desc(pos, lds32(SM_EID + eperm(pos)) >> 23));
        }
        const unsigned head = next_desc(-1, warp);
        asm volatile("bar.sync 5, %0;" ::"n"(NCONS * 32) : "memory");
        STAMP(22);
        consumer(head, warp);
        STAMP(4);
    } else if (warp == NCONS) {
        fence_async();
        cta_sync();
        const unsigned late = issuer(&tmx, p, nst, T0);
#pragma unroll 1
        for (int i = 0; i < 4; i++) {
            bwait(SM_EMPTY + (nst + i - NX) * 8);
            if (elect()) { bar_expect(wbar + i * 8, 16384); tma_2d(SB + i * 16384, &tmw, wbar + i * 8, i * 64, 0); }
        }
#ifdef DBG_TR
        for (int i = lane; i < nst; i += 32) g_trace[(cta * 180 + i) * 4 + 3] = lds32(SM_TR + i * 8) - T0;
#endif
#ifdef DBG_H
        STAMPW(8, late); STAMPW(7, T0 - tstart); STAMPW(14, nst);
#endif
        cta_sync();
    } else {
        const unsigned ewait = recorder(p, warp - NCONS - 1, nst);
#ifdef DBG_H
        if (warp == 15) STAMPW(12, ewait); else STAMPW(11, ewait);
#endif
        cta_sync();
    }

    const int wg = warp >> 2, wq = warp & 3;
    int ln;
    asm volatile("mov.u32 %0, %%laneid;" : "=r"(ln));
    const bool lead = wq == 0 && ln == 0;
    unsigned af[16][4];
    const unsigned wt = SB + wg * 16384;
    const unsigned wa = wt + (((ln >> 4) * 8 + (ln & 7)) << 7) + (((2 * wq + ((ln >> 3) & 1)) ^ (ln & 7)) << 4);
    bwait(wbar + wg * 8);
#pragma unroll
    for (int k = 0; k < 8; k++) ldsm4t(af[k], wa + k * 2048);
    fence_async();
    cta_sync();
    STAMP(5);
    if (lead) { bar_expect(wbar + 32 + wg * 8, 16384); tma_2d(wt, &tmw, wbar + 32 + wg * 8, wg * 64, 128); }
    const uint64_t desc0 = (uint64_t)(((SM_H) >> 4) & 0x3FFF) | (1ull << 16) | (64ull << 32) | (1ull << 62);
    float d[32];
    const int row0 = cta * (NPC * 4);
    wg_fence();
#pragma unroll
    for (int k = 0; k < 8; k++) wgmma_rs<64>(d, af[k], desc0 + (k >> 2) * (HPANEL >> 4) + (k & 3) * 2, k != 0);
    wg_commit();
    bwait(wbar + 32 + wg * 8);
#pragma unroll
    for (int k = 0; k < 8; k++) ldsm4t(af[8 + k], wa + k * 2048);
    wg_fence();
#pragma unroll
    for (int k = 8; k < 16; k++) wgmma_rs<64>(d, af[k], desc0 + (k >> 2) * (HPANEL >> 4) + (k & 3) * 2, 1);
    wg_commit();
    wg_wait0();
    out_chunk<64>(d, wt, &tmo, wg, row0, true, wa, lead);
#pragma unroll 1
    for (int c = 1; c < 4; c++) {
        wg_fence();
#pragma unroll
        for (int k = 0; k < 16; k++) wgmma_rs<64>(d, af[k], desc0 + c * 512 + (k >> 2) * (HPANEL >> 4) + (k & 3) * 2, k != 0);
        wg_commit();
        wg_wait0();
        out_chunk<64>(d, wt, &tmo, wg, row0 + c * 64, false, wa, lead);
    }
    wg_fence();
#pragma unroll
    for (int k = 0; k < 16; k++) wgmma_rs<48>(d, af[k], desc0 + 4 * 512 + (k >> 2) * (HPANEL >> 4) + (k & 3) * 2, k != 0);
    wg_commit();
    wg_wait0();
    out_chunk<48>(d, wt, &tmo, wg, row0 + 256, false, wa, lead);
    if (lead) asm volatile("cp.async.bulk.wait_group.read 0;" ::: "memory");
    STAMP(6);
#ifdef DBG_GT
    { unsigned g; asm volatile("mov.u32 %0, %%globaltimer_lo;" : "=r"(g)); STAMPW(30, g); }
#endif
}

typedef CUresult (*EncFn)(CUtensorMap*, CUtensorMapDataType, cuuint32_t, void*, const cuuint64_t*, const cuuint64_t*, const cuuint32_t*,
                          const cuuint32_t*, CUtensorMapInterleave, CUtensorMapSwizzle, CUtensorMapL2promotion, CUtensorMapFloatOOBfill);

extern "C" void kernel_launch(void* const* d_in, const int* in_sizes, int n_in, void* d_out, int out_size) {
    static EncFn enc = nullptr;
    static int nsm = 0;
    if (!enc) {
        void* fn = nullptr; cudaDriverEntryPointQueryResult qr;
        cudaGetDriverEntryPoint("cuTensorMapEncodeTiled", &fn, cudaEnableDefault, &qr);
        enc = (EncFn)fn;
        int dev = 0; cudaGetDevice(&dev);
        cudaDeviceGetAttribute(&nsm, cudaDevAttrMultiProcessorCount, dev);
        cudaFuncSetAttribute(mace_kernel, cudaFuncAttributeMaxDynamicSharedMemorySize, SM_TOTAL);
    }
    Params p;
    p.x = (const __nv_bfloat16*)d_in[0]; p.src = (const int*)d_in[1]; p.dst = (const int*)d_in[2];
    p.sh = (const __nv_bfloat16*)d_in[3]; p.ea = (const __nv_bfloat16*)d_in[4]; p.cg = (const __nv_bfloat16*)d_in[5];
    p.wr = (const __nv_bfloat16*)d_in[6]; p.wo = (const __nv_bfloat16*)d_in[7];
    p.N = in_sizes[0] / 1024; p.E = in_sizes[1];
    p.fast = (nsm >= NCTA && p.N <= NCTA * NPC && p.E <= NCTA * EPC && p.E > 0 && p.N > 1 && (p.E & 3) == 0) ? 1 : 0;
    p.rate = (unsigned)((double)PACE * ((double)p.E / 160000.0) * 256.0 / (double)p.N);
    p.zero = 0;
    CUtensorMap tmx, tmw, tmo;
    const cuuint32_t es[3] = {1, 1, 1};
    {
        cuuint64_t dims[3] = {64, (cuuint64_t)p.N * 4, 4}; cuuint64_t str[2] = {512, 128}; cuuint32_t box[3] = {64, 4, 4};
        enc(&tmx, CU_TENSOR_MAP_DATA_TYPE_BFLOAT16, 3, d_in[0], dims, str, box, es, CU_TENSOR_MAP_INTERLEAVE_NONE, CU_TENSOR_MAP_SWIZZLE_128B, CU_TENSOR_MAP_L2_PROMOTION_NONE, CU_TENSOR_MAP_FLOAT_OOB_FILL_NONE);
    }
    {
        cuuint64_t dims[2] = {256, 256}; cuuint64_t str[1] = {512}; cuuint32_t box[2] = {64, 128};
        enc(&tmw, CU_TENSOR_MAP_DATA_TYPE_BFLOAT16, 2, d_in[7], dims, str, box, es, CU_TENSOR_MAP_INTERLEAVE_NONE, CU_TENSOR_MAP_SWIZZLE_128B, CU_TENSOR_MAP_L2_PROMOTION_NONE, CU_TENSOR_MAP_FLOAT_OOB_FILL_NONE);
    }
    {
        cuuint64_t dims[2] = {256, (cuuint64_t)p.N * 4}; cuuint64_t str[1] = {512}; cuuint32_t box[2] = {64, 16};
        enc(&tmo, CU_TENSOR_MAP_DATA_TYPE_BFLOAT16, 2, d_out, dims, str, box, es, CU_TENSOR_MAP_INTERLEAVE_NONE, CU_TENSOR_MAP_SWIZZLE_128B, CU_TENSOR_MAP_L2_PROMOTION_NONE, CU_TENSOR_MAP_FLOAT_OOB_FILL_NONE);
    }
    const int grid = p.fast ? NCTA : (p.N + NPC - 1) / NPC;
    mace_kernel<<<grid, 512, SM_TOTAL>>>(tmx, tmw, tmo, p);
}
```

```cpp
#include <cuda_runtime.h>
#include <cuda_bf16.h>
#include <cuda.h>
#include <stdint.h>

#ifndef NX
#define NX 10
#endif
#ifndef NR
#define NR 9
#endif
#ifndef PACE
#define PACE 50000
#endif
#ifndef T0DELTA
#define T0DELTA 5700
#endif
#ifndef BSH
#define BSH 4
#endif
#ifndef POLLT
#define POLLT 2900
#endif
#ifndef PF0
#define PF0 1000
#endif
#ifndef PFD
#define PFD 0
#endif
#ifndef PFLEAD
#define PFLEAD 8
#endif
#ifndef RSPL
#define RSPL 10
#endif
#ifndef RLDG
#define RLDG "ld.global.nc"
#endif
#ifndef DISP
#define DISP 1
#endif
#ifndef XST
#define XST "st.relaxed.gpu.global.v4.u32"
#endif
#define NCTA 132
#define NPC 76
#define EPC 1216
#define NCH 10
#define CAP 1376
#define CAPP 1440
#define NCONS 13
#define RSTR 608
#define NBW ((((NCTA * NPC) >> BSH) + 128) / 128)

#define SB 1024
#define SM_X SB
#define SM_R (SM_X + NX * 16384)
#define SM_EID (SM_R + NR * 8 * RSTR)
#define SM_NEXT (SM_EID + 6144)
#define SM_H (SB + 65536)
#define HPANEL 38912
#define SM_FULL (SM_H + 4 * HPANEL)
#define SM_EMPTY (SM_FULL + CAPP + 128)
#define SM_SRC (SM_EMPTY + CAPP)
#define SM_BITS (SM_SRC + 1392 * 4)
#define SM_MISC (SM_BITS + 2544)
#define SM_TOTAL (SM_MISC + 128 - SB)
#define NXT 448
#define SM_STAGE SM_R
#define SM_CNT (SM_R + NXT * 48)
#define SM_WR (SM_CNT + 640)
#define SM_BKT (SM_WR + 16 * 528)
static_assert(SM_BKT + NBW * 512 + 128 <= SM_EID, "smem");
#define DUM ((unsigned)(NBW * 128) << (18 + BSH))
#define BW 45
static_assert(SM_NEXT + CAPP * 4 <= SM_FULL && SM_TOTAL <= 232448, "smem");
#define STR_(x) #x
#define STR(x) STR_(x)

__device__ uint4 g_xch[NCTA * NCTA * NCH + 8];
#ifdef DBG_TIMES
extern "C" { __device__ unsigned g_times[NCTA * 32]; }
#define STAMPV(m, i, v) asm volatile("{.reg .pred q; .reg .b32 t; .reg .b64 a, b; mov.u32 t, %%tid.x; and.b32 t, t, %0; setp.eq.u32 q, t, 0; mov.u32 t, %%ctaid.x; mov.u64 b, g_times; mad.wide.u32 a, t, 128, b; @q st.global.u32 [a+%1], %2;}" ::"n"(m), "n"((i) * 4), "r"(v) : "memory")
#define STAMP(i) STAMPV(1023, i, clk() | 0x1)
#define STAMPL(i) if (wid == 0) STAMPW(i, clk() | 0x1)
#define STAMPW(i, v) asm volatile("{.reg .b32 t; .reg .b64 a, b; mov.u32 t, %%ctaid.x; mov.u64 b, g_times; mad.wide.u32 a, t, 128, b; st.global.u32 [a+%0], %1;}" ::"n"((i) * 4), "r"(v) : "memory")
#define TK(i, dep) unsigned tk##i; asm volatile("{.reg .b32 t; and.b32 t, %1, %2; mov.u32 %0, %%clock; add.u32 %0, %0, t;}" : "=r"(tk##i) : "r"(dep), "r"(p.zero) : "memory")
#define TKO(i) STAMPV(1023, i, tk##i | 1)
#else
#define STAMP(i)
#define STAMPL(i)
#define STAMPV(m, i, v)
#define STAMPW(i, v)
#define TK(i, dep)
#define TKO(i)
#endif

struct Params {
    const int* src; const int* dst; uint4* xch; const __nv_bfloat16* wr;
    int Ef, N;
    const __nv_bfloat16* cg; const __nv_bfloat16* x; const __nv_bfloat16* sh; const __nv_bfloat16* ea; const __nv_bfloat16* wo;
    int E; unsigned rate, zero;
};

__device__ __forceinline__ unsigned clk() { unsigned c; asm volatile("mov.u32 %0, %%clock;" : "=r"(c)); return c; }
__device__ __forceinline__ bool elect() { unsigned p; asm volatile("{.reg .pred P; elect.sync _|P, 0xffffffff; selp.u32 %0,1,0,P;}" : "=r"(p)); return p; }
__device__ __forceinline__ bool try_wait(unsigned a) { unsigned ok; asm volatile("{.reg .pred p; mbarrier.try_wait.parity.shared::cta.b64 p,[%1],0; selp.u32 %0,1,0,p;}" : "=r"(ok) : "r"(a) : "memory"); return ok; }
__device__ __forceinline__ void bwait(unsigned a) { if (!try_wait(a)) { for (int i = 0; i < (1 << 18) && !try_wait(a); i++); } }
__device__ __forceinline__ unsigned pin(unsigned x) { unsigned y; asm volatile("mov.u32 %0, %1;" : "=r"(y) : "r"(x)); return y; }
__device__ __forceinline__ const char* pin64(const char* x) { const char* y; asm volatile("mov.u64 %0, %1;" : "=l"(y) : "l"(x)); return y; }
__device__ __forceinline__ void split(unsigned x, unsigned c) { asm volatile("{.reg .pred p; setp.eq.u32 p, %0, %1; @p exit;}" ::"r"(x), "r"(c) : "memory"); }
__device__ __forceinline__ void bar_init(unsigned a, unsigned c) { asm volatile("mbarrier.init.shared::cta.b64 [%0], %1;" ::"r"(a), "r"(c) : "memory"); }
__device__ __forceinline__ void bar_expect(unsigned a, unsigned bytes) { asm volatile("mbarrier.arrive.expect_tx.shared::cta.b64 _, [%0], %1;" ::"r"(a), "r"(bytes) : "memory"); }
__device__ __forceinline__ void bar_complete(unsigned a, unsigned bytes) { asm volatile("mbarrier.complete_tx.relaxed.cta.shared::cta.b64 [%0], %1;" ::"r"(a), "r"(bytes) : "memory"); }
__device__ __forceinline__ void fence_async() { asm volatile("fence.proxy.async.shared::cta;" ::: "memory"); }
template <int ID, int N> __device__ __forceinline__ void nsync() { asm volatile("bar.sync %0, %1;" ::"n"(ID), "n"(N) : "memory"); }
template <int ID, int N> __device__ __forceinline__ void narrive() { asm volatile("bar.arrive %0, %1;" ::"n"(ID), "n"(N) : "memory"); }
__device__ __forceinline__ void cta_sync() { asm volatile("bar.sync 0, 512;" ::: "memory"); }
__device__ __forceinline__ unsigned lds32(unsigned a) { unsigned v; asm volatile("ld.shared.u32 %0,[%1];" : "=r"(v) : "r"(a) : "memory"); return v; }
__device__ __forceinline__ unsigned lds16(unsigned a) { unsigned v; asm volatile("ld.shared.u16 %0,[%1];" : "=r"(v) : "r"(a) : "memory"); return v; }
__device__ __forceinline__ uint4 lds128(unsigned a) { uint4 v; asm volatile("ld.shared.v4.u32 {%0,%1,%2,%3},[%4];" : "=r"(v.x), "=r"(v.y), "=r"(v.z), "=r"(v.w) : "r"(a) : "memory"); return v; }
__device__ __forceinline__ void sts32(unsigned a, unsigned v) { asm volatile("st.shared.u32 [%0],%1;" ::"r"(a), "r"(v) : "memory"); }
__device__ __forceinline__ void sts16(unsigned a, unsigned v) { asm volatile("st.shared.u16 [%0],%1;" ::"r"(a), "r"(v) : "memory"); }
__device__ __forceinline__ void sts64(unsigned a, unsigned x, unsigned y) { asm volatile("st.shared.v2.u32 [%0],{%1,%2};" ::"r"(a), "r"(x), "r"(y) : "memory"); }
__device__ __forceinline__ void sts128(unsigned a, unsigned x, unsigned y, unsigned z, unsigned w) { asm volatile("st.shared.v4.u32 [%0],{%1,%2,%3,%4};" ::"r"(a), "r"(x), "r"(y), "r"(z), "r"(w) : "memory"); }
__device__ __forceinline__ unsigned atoms_add(unsigned a, unsigned v) { unsigned o; asm volatile("atom.shared.add.u32 %0,[%1],%2;" : "=r"(o) : "r"(a), "r"(v) : "memory"); return o; }
__device__ __forceinline__ void ldsm4t(unsigned* r, unsigned a) { asm volatile("ldmatrix.sync.aligned.m8n8.x4.trans.shared.b16 {%0,%1,%2,%3},[%4];" : "=r"(r[0]), "=r"(r[1]), "=r"(r[2]), "=r"(r[3]) : "r"(a) : "memory"); }
__device__ __forceinline__ void stsm4t(unsigned a, unsigned r0, unsigned r1, unsigned r2, unsigned r3) { asm volatile("stmatrix.sync.aligned.m8n8.x4.trans.shared.b16 [%0],{%1,%2,%3,%4};" ::"r"(a), "r"(r0), "r"(r1), "r"(r2), "r"(r3) : "memory"); }
__device__ __forceinline__ unsigned pack2(float lo, float hi) { unsigned p; asm("cvt.rn.bf16x2.f32 %0,%1,%2;" : "=r"(p) : "f"(hi), "f"(lo)); return p; }
__device__ __forceinline__ void mma1688(float* d, unsigned a0, unsigned a1, unsigned b0) {
    asm("mma.sync.aligned.m16n8k8.row.col.f32.bf16.bf16.f32 {%0,%1,%2,%3},{%4,%5},{%6},{%7,%7,%7,%7};"
        : "=f"(d[0]), "=f"(d[1]), "=f"(d[2]), "=f"(d[3]) : "r"(a0), "r"(a1), "r"(b0), "f"(0.f));
}
__device__ __forceinline__ void mma16816(float* d, const unsigned* a, unsigned b0, unsigned b1) {
    asm volatile("mma.sync.aligned.m16n8k16.row.col.f32.bf16.bf16.f32 {%0,%1,%2,%3},{%4,%5,%6,%7},{%8,%9},{%10,%10,%10,%10};"
        : "=f"(d[0]), "=f"(d[1]), "=f"(d[2]), "=f"(d[3]) : "r"(a[0]), "r"(a[1]), "r"(a[2]), "r"(a[3]), "r"(b0), "r"(b1), "f"(0.f));
}
__device__ __forceinline__ void tma_x(unsigned da, const void* tm, unsigned ba, int c1) {
    asm volatile("cp.async.bulk.tensor.3d.shared::cluster.global.mbarrier::complete_tx::bytes [%0], [%1, {%3,%4,%3}], [%2];" ::"r"(da), "l"(tm), "r"(ba), "r"(0), "r"(c1) : "memory");
}
__device__ __forceinline__ void tma_2d(unsigned da, const CUtensorMap* tm, unsigned ba, int c0, int c1) {
    asm volatile("cp.async.bulk.tensor.2d.shared::cluster.global.mbarrier::complete_tx::bytes [%0], [%1, {%3,%4}], [%2];" ::"r"(da), "l"(tm), "r"(ba), "r"(c0), "r"(c1) : "memory");
}
__device__ __forceinline__ void tma_st(const CUtensorMap* tm, unsigned sa, int c0, int c1) {
    asm volatile("cp.async.bulk.tensor.2d.global.shared::cta.bulk_group [%0, {%2,%3}], [%1];" ::"l"(tm), "r"(sa), "r"(c0), "r"(c1) : "memory");
}
__device__ __forceinline__ void pf_l2(const void* p, unsigned bytes) { asm volatile("cp.async.bulk.prefetch.L2.global [%0], %1;" ::"l"(p), "r"(bytes) : "memory"); }

#define WG_REGS24(d) "+f"(d[0]), "+f"(d[1]), "+f"(d[2]), "+f"(d[3]), "+f"(d[4]), "+f"(d[5]), "+f"(d[6]), "+f"(d[7]), \
    "+f"(d[8]), "+f"(d[9]), "+f"(d[10]), "+f"(d[11]), "+f"(d[12]), "+f"(d[13]), "+f"(d[14]), "+f"(d[15]), \
    "+f"(d[16]), "+f"(d[17]), "+f"(d[18]), "+f"(d[19]), "+f"(d[20]), "+f"(d[21]), "+f"(d[22]), "+f"(d[23])
template <int NN> __device__ __forceinline__ void wgmma_rs(float* d, const unsigned* a, uint64_t desc, int scale_d);
template <> __device__ __forceinline__ void wgmma_rs<48>(float* d, const unsigned* a, uint64_t desc, int scale_d) {
    asm volatile("{.reg .pred p; setp.ne.b32 p, %29, 0;\n"
        "wgmma.mma_async.sync.aligned.m64n48k16.f32.bf16.bf16 {%0,%1,%2,%3,%4,%5,%6,%7,%8,%9,%10,%11,%12,%13,%14,%15,%16,%17,%18,%19,"
        "%20,%21,%22,%23}, {%24,%25,%26,%27}, %28, p, 1, 1, 0;}"
        : WG_REGS24(d)
        : "r"(a[0]), "r"(a[1]), "r"(a[2]), "r"(a[3]), "l"(desc), "r"(scale_d));
}
template <> __device__ __forceinline__ void wgmma_rs<64>(float* d, const unsigned* a, uint64_t desc, int scale_d) {
    asm volatile("{.reg .pred p; setp.ne.b32 p, %37, 0;\n"
        "wgmma.mma_async.sync.aligned.m64n64k16.f32.bf16.bf16 {%0,%1,%2,%3,%4,%5,%6,%7,%8,%9,%10,%11,%12,%13,%14,%15,%16,%17,%18,%19,"
        "%20,%21,%22,%23,%24,%25,%26,%27,%28,%29,%30,%31}, {%32,%33,%34,%35}, %36, p, 1, 1, 0;}"
        : WG_REGS24(d), "+f"(d[24]), "+f"(d[25]), "+f"(d[26]), "+f"(d[27]), "+f"(d[28]), "+f"(d[29]), "+f"(d[30]), "+f"(d[31])
        : "r"(a[0]), "r"(a[1]), "r"(a[2]), "r"(a[3]), "l"(desc), "r"(scale_d));
}
__device__ __forceinline__ void wg_fence() { asm volatile("wgmma.fence.sync.aligned;" ::: "memory"); }
__device__ __forceinline__ void wg_commit() { asm volatile("wgmma.commit_group.sync.aligned;" ::: "memory"); }
__device__ __forceinline__ void wg_wait0() { asm volatile("wgmma.wait_group.sync.aligned 0;" ::: "memory"); }

#define PF(D, RW, K, J0, J1) \
    "cvt.rn.bf16x2.f32 t0, " #D "1, " #D "0;\n cvt.rn.bf16x2.f32 t1, " #D "3, " #D "2;\n" \
    "mov.b32 {lo, hi}, " #RW ";\n mov.b32 u0, {lo, lo};\n mov.b32 u1, {hi, hi};\n" \
    "fma.rn.bf16x2 a" #K "_" #J0 ", t0, u0, a" #K "_" #J0 ";\n fma.rn.bf16x2 a" #K "_" #J1 ", t1, u1, a" #K "_" #J1 ";\n"
#define MMA(D, A0, A1) "mma.sync.aligned.m16n8k8.row.col.f32.bf16.bf16.f32 {" #D "0," #D "1," #D "2," #D "3}, {" #A0 "," #A1 "}, {bf}, {fz,fz,fz,fz};\n"
#define LDX(X, OFF) "ldmatrix.sync.aligned.m8n8.x4.trans.shared.b16 {" #X "0," #X "1," #X "2," #X "3}, [xa+" STR(SM_X) "+" #OFF "];\n"
#define DECODE \
    "lop3.b32 xa, dn, 0x3F800, %1, 0xEA;\n" \
    "shr.u32 t2, dn, 21;\n mad.lo.u32 ra, t2, 32, %2;\n mad.lo.u32 ca, t2, 32, %3;\n" \
    "and.b32 t3, dn, 0x7FF;\n shl.b32 t3, t3, 2;\n" SETD
#define LOADS \
    LDX(x, 0) LDX(y, 512) \
    "@act ld.shared.u32 bf, [ca+" STR(SM_R) "];\n" \
    "ld.shared.v4.u32 {r0,r1,r2,r3}, [ra+" STR(SM_R) "];\n" \
    "ld.shared.u32 dn, [t3+" STR(SM_NEXT) "];\n"
#if DISP == 0
#define SETD "bfe.u32 ix, dn, 18, 3;\n"
#define DISPATCH "brx.idx.uni ix, TS;\n"
#define T23
#define T45
#else
#define SETD "and.b32 ix, dn, 0x40000;\n setp.ne.u32 q0, ix, 0;\n and.b32 ix, dn, 0x80000;\n setp.ne.u32 q1, ix, 0;\n and.b32 ix, dn, 0x100000;\n setp.ne.u32 q2, ix, 0;\n"
#define DISPATCH "@q2 bra.uni T45;\n @q1 bra.uni T23;\n @q0 bra.uni B1;\n bra.uni B0;\n"
#define T23 "T23:\n @q0 bra.uni B3;\n"
#define T45 "T45:\n @q1 bra.uni FIN;\n @q0 bra.uni B5;\n"
#endif
#ifdef XCONS
#define BODY(K) "B" #K ":\n" \
    "xor.b32 x0, x0, y0;\n xor.b32 r0, r0, r3;\n" MMA(d, x0, x1) LDX(x, 1024) LDX(y, 1536) \
    "and.b32 bn, dn, 0x7F8;\n" \
    "mbarrier.test_wait.parity.shared::cta.b64 p, [bn+" STR(SM_FULL) "], 0;\n" \
    "ld.shared.v4.u32 {s0,s1,s2,s3}, [ra+" STR(SM_R) "+128];\n" \
    PF(d, r0, K, 0, 1) "xor.b32 x0, x0, y0;\n" MMA(d, x0, x1) \
    "@l0 mbarrier.arrive.shared::cta.b64 _, [bc+" STR(SM_EMPTY) "];\n" \
    "mov.u32 bc, bn;\n" DECODE \
    "@!p bra.uni W" #K ";\n" \
    "R" #K ":\n" LOADS \
    PF(d, s2, K, 12, 13) DISPATCH
#else
#define BODY(K) "B" #K ":\n" \
    MMA(d, x0, x1) MMA(e, x2, x3) LDX(x, 1024) \
    "and.b32 bn, dn, 0x7F8;\n" \
    "mbarrier.test_wait.parity.shared::cta.b64 p, [bn+" STR(SM_FULL) "], 0;\n" \
    PF(d, r0, K, 0, 1) MMA(d, y0, y1) PF(e, r1, K, 2, 3) MMA(e, y2, y3) LDX(y, 1536) \
    "ld.shared.v4.u32 {s0,s1,s2,s3}, [ra+" STR(SM_R) "+128];\n" \
    PF(d, r2, K, 4, 5) MMA(d, x0, x1) PF(e, r3, K, 6, 7) MMA(e, x2, x3) \
    PF(d, s0, K, 8, 9) MMA(d, y0, y1) \
    "@l0 mbarrier.arrive.shared::cta.b64 _, [bc+" STR(SM_EMPTY) "];\n" \
    PF(e, s1, K, 10, 11) MMA(e, y2, y3) \
    "mov.u32 bc, bn;\n" DECODE \
    "@!p bra.uni W" #K ";\n" \
    "R" #K ":\n" LOADS \
    PF(d, s2, K, 12, 13) PF(e, s3, K, 14, 15) DISPATCH
#endif
#ifdef DBG_TR
#define SM_TR (SM_NEXT + CAPP * 4)
#define TRC "mov.u32 t1, %%clock;\n st.shared.u32 [bc+" STR(SM_TR) "], t1;\n"
extern "C" { __device__ unsigned g_trace[NCTA * 4 * 180]; }
#else
#define TRC
#endif
#define WAIT(K) "W" #K ":\n mov.u32 t0, 0;\n" \
    "V" #K ":\n mbarrier.try_wait.parity.shared::cta.b64 p, [bc+" STR(SM_FULL) "], 0;\n" TRC "@p bra.uni R" #K ";\n" \
    "add.u32 t0, t0, 1;\n setp.lt.u32 p, t0, 400000;\n @p bra.uni V" #K ";\n bra.uni R" #K ";\n"
#define Z4(K, A, B, C, D) "mov.u32 a" #K "_" #A ", 0; mov.u32 a" #K "_" #B ", 0; mov.u32 a" #K "_" #C ", 0; mov.u32 a" #K "_" #D ", 0;\n"
#define ZACC(K) Z4(K, 0, 1, 2, 3) Z4(K, 4, 5, 6, 7) Z4(K, 8, 9, 10, 11) Z4(K, 12, 13, 14, 15)
#define ST4(K, A, B, C, D, R, P) "stmatrix.sync.aligned.m8n8.x4.trans.shared.b16 [" #R "+" STR(SM_H) "+" #K "*512+" #P "*" STR(HPANEL) "], {a" #K "_" #A ",a" #K "_" #B ",a" #K "_" #C ",a" #K "_" #D "};\n"
#define STH(K, R0, R1) ST4(K, 0, 1, 2, 3, R0, 0) ST4(K, 4, 5, 6, 7, R1, 1) ST4(K, 8, 9, 10, 11, R0, 2) ST4(K, 12, 13, 14, 15, R1, 3)
__device__ __forceinline__ unsigned consumer(unsigned head) {
    const int lane = threadIdx.x & 31, g = lane >> 2, t = lane & 3;
    const unsigned xl = (lane & 3) * 128 + ((((lane >> 3) + (lane & 4)) ^ (lane & 3)) << 4);
    const unsigned rl = (t >> 1) * 320 + g * 16;
    const unsigned cl = (t >> 1) == (g >> 2) ? 256 + (2 * (g & 3) + (t & 1)) * 4 : 0;
    asm volatile("{\n"
        ".reg .b32 a0_<16>, a1_<16>, a2_<16>, a3_<16>, a4_<16>, a5_<16>;\n"
        ".reg .b32 x<4>, y<4>, r<4>, s<4>, t<4>, u<2>, bf, xa, ra, ca, bn, bc, dn, ix;\n"
        ".reg .f32 d<4>, e<4>, fz;\n .reg .b16 lo, hi;\n .reg .pred p, q<3>, act, l0;\n"
#if DISP == 0
        "TS: .branchtargets B0, B1, B2, B3, B4, B5, FIN, FIN;\n"
#endif
        "mov.f32 fz, 0f00000000;\n mov.u32 bf, 0;\n setp.ne.u32 act, %3, 0;\n setp.eq.u32 l0, %1, 0;\n mov.u32 dn, %0;\n"
        ZACC(0) ZACC(1) ZACC(2) ZACC(3) ZACC(4) ZACC(5)
        "and.b32 bc, dn, 0x7F8;\n"
        DECODE "and.b32 t0, dn, 0x1C0000;\n setp.eq.u32 p, t0, 0x1C0000;\n @p bra.uni FIN;\n"
        WAIT(6)
        "R6:\n" LOADS DISPATCH
        BODY(0) BODY(1) T23 BODY(2) BODY(3) T45 BODY(4) BODY(5)
        WAIT(0) WAIT(1) WAIT(2) WAIT(3) WAIT(4) WAIT(5)
        "FIN:\n bar.sync 0, 512;\n"
        "sub.u32 t0, ra, %2;\n shr.u32 %0, t0, 5;\n mad.lo.u32 t0, t0, 96, %1;\n xor.b32 t1, t0, 64;\n"
        STH(0, t0, t1) STH(1, t1, t0) STH(2, t0, t1) STH(3, t1, t0)
        "setp.eq.u32 p, %0, 12;\n @p bra.uni DONE;\n"
        STH(4, t0, t1) STH(5, t1, t0)
        "DONE:\n}\n" : "+r"(head) : "r"(xl), "r"(rl), "r"(cl) : "memory");
    return head;
}

#define RMMA(D, Q, B0, B1) "mma.sync.aligned.m16n8k16.row.col.f32.bf16.bf16.f32 {" #D "0," #D "1," #D "2," #D "3}, {w" #Q "_0,w" #Q "_1,w" #Q "_2,w" #Q "_3}, {" #B0 "," #B1 "}, {fz,fz,fz,fz};\n"
#define RPK(I, D) "cvt.rn.bf16x2.f32 u" #I ", " #D "2, " #D "0;\n cvt.rn.bf16x2.f32 v" #I ", " #D "3, " #D "1;\n"
#define RG(Q0, Q1, Q2, Q3, B0, B1, A, OFF) \
    RMMA(da, Q0, B0, B1) RMMA(db, Q1, B0, B1) RMMA(dc, Q2, B0, B1) RMMA(dd, Q3, B0, B1) \
    RPK(0, da) RPK(1, db) RPK(2, dc) RPK(3, dd) \
    "st.shared.v4.u32 [" #A "+" #OFF "], {u0,u1,u2,u3};\n st.shared.v4.u32 [" #A "+" #OFF "+4*" STR(RSTR) "], {v0,v1,v2,v3};\n"
#define RSPLIT(M) "setp.eq.u32 pk, ro, " #M ";\n @pk exit;\n"
#if RSPL & 2
#define RS1 RSPLIT(1)
#else
#define RS1
#endif
#if RSPL & 4
#define RS2 RSPLIT(2)
#else
#define RS2
#endif
#if RSPL & 8
#define RS3 RSPLIT(3)
#else
#define RS3
#endif
#ifdef NOLOAD
#define RTX "0"
#else
#define RTX "16384"
#endif
#ifdef DBG_R
#define RW0 "mov.u32 tw, %%clock;\n"
#define RW1 "mov.u32 t0, %%clock;\n sub.u32 t0, t0, tw;\n add.u32 %0, %0, t0;\n"
#else
#define RW0
#define RW1
#endif
#ifdef XREC
#define RG2(B0, B1)
#else
#define RG2(B0, B1) RG(8, 9, 10, 11, B0, B1, a0, 128) RS3 RG(12, 13, 14, 15, B0, B1, a0, 448)
#endif
#define RSTAGE(ID, B0, B1, SEL, PRE, MID) \
    "@!pw bra.uni RW" #ID ";\n RR" #ID ":\n" PRE \
    "mbarrier.test_wait.parity.shared::cta.b64 pw, [sb+" STR(SM_EMPTY) "+16-8*" STR(NR) "], 0;\n" \
    "add.u32 a0, ro, %2;\n add.u32 a2, ro, %4;\n" \
    RG(0, 1, 2, 3, B0, B1, a0, 0) RS1 RG(4, 5, 6, 7, B0, B1, a0, 320) RS2 MID \
    "selp.b32 t0, " SEL ", pe;\n" \
    "mma.sync.aligned.m16n8k8.row.col.f32.bf16.bf16.f32 {da0,da1,da2,da3}, {%5,%6}, {t0}, {fz,fz,fz,fz};\n" RPK(0, da) \
    "st.shared.u32 [a2], u0;\n st.shared.u32 [a2+4*" STR(RSTR) "], v0;\n" \
    RG2(B0, B1) \
    "bar.warp.sync 0xffffffff;\n elect.sync _|l0, 0xffffffff;\n" \
    "@l0 mbarrier.arrive.expect_tx.shared::cta.b64 _, [sb+" STR(SM_FULL) "], " RTX ";\n" \
    "add.u32 sb, sb, 16;\n add.u32 ro, ro, 16*" STR(RSTR) ";\n setp.ge.u32 pk, ro, " STR(SM_EID) ";\n @pk sub.u32 ro, ro, 8*" STR(NR) "*" STR(RSTR) ";\n" \
    "setp.ge.u32 pk, sb, %9;\n @pk bra.uni REND;\n"
#define RWAIT(ID) "RW" #ID ":\n" RW0 "mov.u32 t1, 0;\n" \
    "RV" #ID ":\n mbarrier.try_wait.parity.shared::cta.b64 pk, [sb+" STR(SM_EMPTY) "-8*" STR(NR) "], 0;\n" \
    "add.u32 t1, t1, 1;\n setp.lt.and.u32 pk, t1, 400000, !pk;\n @pk bra.uni RV" #ID ";\n" RW1 "bra.uni RR" #ID ";\n"
#define RLD1(S, I, J, E) "lop3.b32 " #E ", " #E ", 0xFFFFC, tt, 0xEA;\n mad.wide.u32 ad, " #E ", 8, %10;\n " RLDG ".v2.u32 {" #S #I "," #S #J "}, [ad];\n"
#define RLD2(S, I, E, F) "selp.b32 t1, " #E ", " #F ", pe;\n and.b32 t1, t1, -2;\n mad.wide.u32 ad, t1, 2, %11;\n " RLDG ".u32 " #S #I ", [ad];\n"
#define RLOAD(S, DEP) "lop3.b32 tt, " #DEP ", %12, %7, 0xEA;\n" \
    RLD1(S, 0, 1, e0) RLD1(S, 2, 3, e1) RLD2(S, 8, e0, e1) RLD1(S, 4, 5, e2) RLD1(S, 6, 7, e3) RLD2(S, 9, e2, e3)
#define REID1(I) "ld.shared.u32 e" #I ", [ea+" STR(SM_EID) "+64*" #I "];\n"
#define REID REID1(0) REID1(1) REID1(2) REID1(3) "add.u32 ea, ea, 256;\n"
#define RPF "mad.wide.u32 ad, pf, 4096, %14;\n add.u32 pf, pf, 2*" STR(NCTA) ";\n setp.lt.u32 pk, pf, %3;\n selp.b32 pf, pf, %3, pk;\n" \
    "elect.sync _|l0, 0xffffffff;\n @l0 cp.async.bulk.prefetch.L2.global [ad], 4096;\n"
#define RLDW(Q) "ldmatrix.sync.aligned.m8n8.x4.trans.shared.b16 {w" #Q "_0,w" #Q "_1,w" #Q "_2,w" #Q "_3}, [%1+2*(64*(2*(" #Q ">>3)+((" #Q "&3)>>1))+8*((2*(" #Q "&1)+(" #Q "&4))^(2*(" #Q "&2))))];\n"
__device__ __forceinline__ unsigned recorder(const Params& p, int hw, int nst, unsigned cg0, unsigned cg1) {
    const int lane = threadIdx.x & 31, g = lane >> 2, t = lane & 3, mi = lane >> 3, r = lane & 7;
    const unsigned wa = SM_WR + (4 * (r >> 1) + (r & 1) + 2 * (mi >> 1)) * 528 + (mi & 1) * 16;
    unsigned ewait = 0;
    asm volatile("{\n"
        ".reg .b32 w0_<4>, w1_<4>, w2_<4>, w3_<4>, w4_<4>, w5_<4>, w6_<4>, w7_<4>, w8_<4>, w9_<4>, w10_<4>, w11_<4>, w12_<4>, w13_<4>, w14_<4>, w15_<4>;\n"
        ".reg .b32 x<10>, y<10>, e<4>, u<4>, v<4>, a<3>, t<2>, tt, tw, ea, sb, ro, pf;\n .reg .b64 ad;\n"
        ".reg .f32 da<4>, db<4>, dc<4>, dd<4>, fz;\n .reg .pred pw, pk, pe, l0;\n"
        RLDW(0) RLDW(1) RLDW(2) RLDW(3) RLDW(4) RLDW(5) RLDW(6) RLDW(7) RLDW(8) RLDW(9) RLDW(10) RLDW(11) RLDW(12) RLDW(13) RLDW(14) RLDW(15)
        "mov.f32 fz, 0f00000000;\n and.b32 t0, %7, 1;\n setp.eq.u32 pe, t0, 0;\n"
        "mov.u32 pf, %15;\n mad.lo.u32 ea, %13, 32, %8;\n shl.b32 sb, %13, 3;\n mad.lo.u32 ro, %13, 8*" STR(RSTR) ", " STR(SM_R) ";\n"
        "bar.sync 0, 512;\n"
        "setp.lt.u32 pw, sb, %9;\n @!pw bra.uni REND;\n"
        REID RLOAD(x, %12) REID
        "RTOP:\n"
        RSTAGE(0, x0, x1, "x8, 0", RLOAD(y, x0), ) RSTAGE(1, x2, x3, "0, x8", , ) RSTAGE(2, x4, x5, "x9, 0", , RPF) RSTAGE(3, x6, x7, "0, x9", , REID)
        RSTAGE(4, y0, y1, "y8, 0", RLOAD(x, y0), ) RSTAGE(5, y2, y3, "0, y8", , ) RSTAGE(6, y4, y5, "y9, 0", , RPF) RSTAGE(7, y6, y7, "0, y9", , REID)
        "bra.uni RTOP;\n"
        RWAIT(0) RWAIT(1) RWAIT(2) RWAIT(3) RWAIT(4) RWAIT(5) RWAIT(6) RWAIT(7)
        "REND:\n and.b32 t0, sb, 8;\n and.b32 %0, %0, -16;\n or.b32 %0, %0, t0;\n}\n"
        : "+r"(ewait)
        : "r"(wa), "r"(t * RSTR + g * 16), "r"(p.N / 2 - 1), "r"(t * RSTR + 256 + g * 4), "r"(cg0), "r"(cg1), "r"(t),
          "r"(((g >> 1) + 4 * (g & 1)) * 4), "r"(nst * 8), "l"(p.ea), "l"(p.sh), "r"(p.zero), "r"(hw), "l"(p.x),
          "r"(min((int)blockIdx.x + (PFLEAD / 2 + hw) * NCTA, p.N / 2 - 1)) : "memory");
    return ewait;
}
#ifdef NOLOAD
#define TROW(J, Z0, Z1)
#else
#define TROW(J, Z0, Z1) "@l0 cp.async.bulk.tensor.3d.shared::cluster.global.mbarrier::complete_tx::bytes [xs+" #J "*2048], [mp, {" #Z0 ",k" #J "," #Z1 "}], [mb];\n"
#endif
#ifdef DBG_H
#define TL "add.u32 %0, %0, c;\n"
#else
#define TL
#endif
#ifdef DBG_TR
#define TT0 "and.b32 n, sb, -8;\n st.shared.u32 [n+" STR(SM_TR) "], %4;\n shl.b32 n, n, 1;\n cvt.u64.u32 ad, n;\n add.u64 ad, ad, %6;\n sub.u32 n, dl, %4;\n add.u32 c, c, n;\n st.global.v2.u32 [ad], {n, c};\n"
#define TT1 "mov.u32 c, %%clock;\n sub.u32 c, c, %4;\n st.global.u32 [ad+8], c;\n"
#else
#define TT0
#define TT1
#endif
#ifndef TCLK
#define TCLK "mov.u64 ad, %%clock64;\n cvt.u32.u64 c, ad;\n"
#endif
#ifdef SOFT
#define TDL "min.u32 dl, q1, " STR(SOFT) "*4;\n mul.lo.u32 dl, dl, " STR(SOFTR) ";\n mad.lo.u32 dl, q1, rt, dl;\n shr.u32 dl, dl, 10;\n add.u32 dl, dl, %4;\n"
#else
#define TDL "mul.lo.u32 dl, q1, rt;\n shr.u32 dl, dl, 10;\n add.u32 dl, dl, %4;\n"
#endif
__device__ __forceinline__ unsigned issuer(const CUtensorMap* tm, const Params& p, int nst, unsigned T0) {
    unsigned late = 0;
    asm volatile("{\n"
        ".reg .b32 k<4>, q<4>, z<8>, xs, sa, sb, mb, dl, c, n, rt;\n .reg .b64 ad, mp;\n .reg .pred pw, pk, l0;\n"
        "mov.u32 n, " STR(SM_NEXT) ";\n ld.shared.v4.u32 {z0,z1,z2,z3}, [n+-32];\n ld.shared.v4.u32 {z4,z5,z6,z7}, [n+-16];\n"
        "ld.shared.u64 ad, [n+-48];\n add.u64 mp, ad, %1;\n ld.shared.u32 rt, [n+-40];\n add.u32 rt, rt, %5;\n"
        "mov.u32 sb, 0;\n mov.u32 xs, %2;\n mov.u32 mb, " STR(SM_FULL) ";\n"
        "ld.shared.v4.u32 {q0,q1,q2,q3}, [sb+" STR(SM_SRC) "];\n" TDL
        "mov.u32 k0, q0;\n mov.u32 k1, q1;\n mov.u32 k2, q2;\n mov.u32 k3, q3;\n bra.uni TW;\n"
        "TR:\n" TL TT0
        "elect.sync _|l0, 0xffffffff;\n"
        "shl.b32 sa, sb, 2;\n ld.shared.v4.u32 {q0,q1,q2,q3}, [sa+" STR(SM_SRC) "+16];\n"
        "add.u32 sb, sb, 4;\n and.b32 n, sb, -8;\n"
        "mbarrier.test_wait.parity.shared::cta.b64 pw, [n+" STR(SM_EMPTY) "-8*" STR(NX) "], 0;\n"
        TROW(0, z0, z1) TROW(1, z2, z3) TROW(2, z4, z5) TROW(3, z6, z7) TT1 TCLK TDL
        "sub.u32 c, c, dl;\n setp.lt.and.u32 pw, sb, %3, pw;\n setp.ge.and.s32 pw, c, 0, pw;\n"
        "add.u32 mb, n, " STR(SM_FULL) ";\n"
        "add.u32 xs, xs, 8192;\n setp.eq.u32 pk, xs, " STR(SM_R) ";\n selp.b32 xs, " STR(SM_X) ", xs, pk;\n"
        "mov.u32 k0, q0;\n mov.u32 k1, q1;\n mov.u32 k2, q2;\n mov.u32 k3, q3;\n @pw bra.uni TR;\n"
        "TW:\n setp.ge.u32 pk, sb, %3;\n @pk bra.uni TEND;\n mov.u32 n, 0;\n"
        "TV:\n mbarrier.try_wait.parity.shared::cta.b64 pk, [mb+" STR(SM_EMPTY) "-" STR(SM_FULL) "-8*" STR(NX) "], 0;\n"
        "add.u32 n, n, 1;\n setp.lt.and.u32 pk, n, 400000, !pk;\n @pk bra.uni TV;\n"
        "TS:\n" TCLK "sub.u32 c, c, dl;\n setp.lt.s32 pk, c, 0;\n @pk bra.uni TS;\n bra.uni TR;\n"
        "TEND:\n}\n"
        : "+r"(late)
        : "l"(tm), "r"(SM_X + ((NX - nst % NX) % NX) * 16384), "r"(nst * 8), "r"(T0), "r"(p.rate)
#ifdef DBG_TR
          , "l"(g_trace + blockIdx.x * 720)
#endif
        : "memory");
    return late;
}

__device__ __forceinline__ void slow_path(const Params& p) {
    const int lane = threadIdx.x & 31, warp = threadIdx.x >> 5;
#pragma unroll 1
    for (int nl = warp; nl < NPC; nl += 16) {
        const int node = blockIdx.x * NPC + nl;
        float acc[4][8];
#pragma unroll
        for (int w = 0; w < 4; w++)
#pragma unroll
            for (int j = 0; j < 8; j++) acc[w][j] = 0.f;
        if (node < p.N) {
#pragma unroll 1
            for (int e0 = 0; e0 < p.E; e0 += 32) {
                int e = e0 + lane;
                unsigned m = __ballot_sync(~0u, e < p.E && p.dst[e] == node);
                while (m) {
                    int ee = e0 + __ffs(m) - 1; m &= m - 1;
                    int s = p.src[ee];
                    float rw[8];
#pragma unroll
                    for (int j = 0; j < 8; j++) rw[j] = 0.f;
#pragma unroll 1
                    for (int k = 0; k < 16; k++) {
                        float a = __bfloat162float(p.ea[(size_t)ee * 16 + k]);
#pragma unroll
                        for (int j = 0; j < 8; j++) rw[j] += a * __bfloat162float(p.wr[k * 256 + lane * 8 + j]);
                    }
#pragma unroll 1
                    for (int u = 0; u < 4; u++) {
                        float y[8];
#pragma unroll
                        for (int j = 0; j < 8; j++) y[j] = rw[j] * __bfloat162float(p.x[((size_t)s * 4 + u) * 256 + lane * 8 + j]);
#pragma unroll
                        for (int w = 0; w < 4; w++) {
                            float a = 0.f;
#pragma unroll
                            for (int v = 0; v < 4; v++) a += __bfloat162float(p.cg[u * 16 + v * 4 + w]) * __bfloat162float(p.sh[(size_t)ee * 4 + v]);
#pragma unroll
                            for (int j = 0; j < 8; j++) acc[w][j] += a * y[j];
                        }
                    }
                }
            }
        }
#pragma unroll
        for (int w = 0; w < 4; w++) {
            int R = nl * 4 + w;
            sts128(SM_H + (lane >> 3) * HPANEL + R * 128 + (((lane & 7) ^ (R & 7)) << 4),
                   pack2(acc[w][0], acc[w][1]), pack2(acc[w][2], acc[w][3]), pack2(acc[w][4], acc[w][5]), pack2(acc[w][6], acc[w][7]));
        }
    }
}

template <int NN>
__device__ __forceinline__ void out_chunk(float* d, unsigned stg, const CUtensorMap* tmo, int wg, int row0, bool first, unsigned a, bool lead) {
    if (!first) {
        if (lead) asm volatile("cp.async.bulk.wait_group.read 0;" ::: "memory");
    }
    asm volatile("bar.sync %0, 128;" ::"r"(wg + 1) : "memory");
#pragma unroll
    for (int n = 0; n < NN / 8; n += 2)
        stsm4t(a + n * 1024, pack2(d[4 * n], d[4 * n + 1]), pack2(d[4 * n + 2], d[4 * n + 3]), pack2(d[4 * n + 4], d[4 * n + 5]), pack2(d[4 * n + 6], d[4 * n + 7]));
    fence_async();
    asm volatile("bar.sync %0, 128;" ::"r"(wg + 1) : "memory");
    if (lead) {
#pragma unroll
        for (int j = 0; j < NN / 16; j++) tma_st(tmo, stg + j * 2048, wg * 64, row0 + j * 16);
        asm volatile("cp.async.bulk.commit_group;" ::: "memory");
    }
}

__global__ void __launch_bounds__(512, 1)
mace_kernel(const __grid_constant__ Params p, const __grid_constant__ CUtensorMap tmx, const __grid_constant__ CUtensorMap tmw,
            const __grid_constant__ CUtensorMap tmo) {
    extern __shared__ __align__(1024) char smem_raw[];
    const unsigned tstart = clk();
    const int tid = threadIdx.x, cta = blockIdx.x;
    const int e0 = cta * EPC + tid * 4;
    const bool has = tid < EPC / 4 && e0 < p.Ef;
    uint4 s4, d4;
    asm volatile("{.reg .pred q; setp.ne.u32 q, %10, 0;\n @q ld.global.nc.v4.u32 {%0,%1,%2,%3}, [%8];\n @q ld.global.nc.v4.u32 {%4,%5,%6,%7}, [%9];}"
        : "=r"(d4.x), "=r"(d4.y), "=r"(d4.z), "=r"(d4.w), "=r"(s4.x), "=r"(s4.y), "=r"(s4.z), "=r"(s4.w) : "l"(p.dst + e0), "l"(p.src + e0), "r"((int)has) : "memory");
    const int lane = tid & 31, warp = __shfl_sync(~0u, tid >> 5, 0);
    const unsigned wbar = SM_MISC, totA = SM_MISC + 80;
    bool slow = p.Ef == 0;
    int total = 0, nst = 0;
    unsigned T0 = 0, cg0 = 0, cg1 = 0, dsc[4];
    if (slow) {
        if (tid < 8) bar_init(wbar + tid * 8, 1);
    } else if (warp >= NXT / 32) {
        unsigned* const ctr = (unsigned*)(p.xch + NCTA * NCTA * NCH);
        unsigned epn;
        if (warp == 15) {
            asm volatile("ld.relaxed.gpu.global.u32 %0, [%1];" : "=r"(epn) : "l"(ctr));
        } else {
#pragma unroll
            for (int k = 0; k < 6; k++) {
                const unsigned i = lane + k * 32, c = i < CAPP / 16 + 8 || i >= CAPP / 8 + 8 ? 0xFFFFFu : 0xFFFF8u;
                sts128(i < CAPP / 8 + 8 ? SM_FULL + i * 16 : wbar + (i - CAPP / 8 - 8) * 16, c << 1, c << 11, c << 1, c << 11);
            }
            fence_async();
            __syncwarp();
            if (lane < 16) asm volatile("mbarrier.arrive.shared::cta.b64 _, [%0];" ::"r"(SM_EMPTY + (lane - 16) * 8) : "memory");
        }
        uint4 w4[8];
        unsigned c4[4];
#pragma unroll
        for (int k = 0; k < 8; k++) asm volatile("ld.global.nc.v4.u32 {%0,%1,%2,%3}, [%4];" : "=r"(w4[k].x), "=r"(w4[k].y), "=r"(w4[k].z), "=r"(w4[k].w) : "l"((const uint4*)p.wr + (tid - NXT + k * 64)));
#pragma unroll
        for (int k = 0; k < 4; k++) asm volatile("ld.global.nc.u16 %0, [%1];" : "=r"(c4[k]) : "l"(p.cg + (lane & 4) * 8 + (lane & 2) * 4 + (lane >> 3) + (k & 1) * 4 + (k & 2) * 8));
        auto put = [&]() {
#pragma unroll
            for (int k = 0; k < 8; k++) sts128(SM_WR + (warp - NXT / 32 + 2 * k) * 528 + lane * 16, w4[k].x, w4[k].y, w4[k].z, w4[k].w);
            asm volatile("prmt.b32 %0, %2, %3, 0x5410;\n prmt.b32 %1, %4, %5, 0x5410;" : "=&r"(cg0), "=r"(cg1) : "r"(c4[0]), "r"(c4[1]), "r"(c4[2]), "r"(c4[3]));
        };
        if (warp == 15) {
            epn = (epn | 255) + 1;
            sts64(totA, epn, 0);
            narrive<7, NXT + 32>();
            nsync<10, NXT + 32>();
            if (lane == 0) asm volatile("red.relaxed.gpu.global.add.u32 [%0], %1;" ::"l"(ctr), "r"(cta ? 1 : 257 - NCTA) : "memory");
            put();
            while (clk() - tstart < POLLT);
            unsigned v; int it = 0;
            do asm volatile("ld.relaxed.gpu.global.u32 %0, [%1];" : "=r"(v) : "l"(ctr) : "memory");
            while (v != epn && ++it < 4096);
            narrive<8, NXT + 32>();
#ifdef DBG_TIMES
            sts32(totA + 16, it * 2);
#endif
            nsync<9, NXT + 32>();
            uint4 u[NBW];
#pragma unroll
            for (int q = 0; q < NBW; q++) u[q] = lds128(SM_BKT + (lane * NBW + q) * 16);
            const unsigned mx = lds32(SM_CNT + min(lane, NXT / 32 - 1) * 4), bad = lds32(totA + 4);
            unsigned sum = 0;
#pragma unroll
            for (int q = 0; q < NBW; q++) sum += u[q].x + u[q].y + u[q].z + u[q].w;
            unsigned inc = sum;
#pragma unroll
            for (int o = 1; o < 32; o <<= 1) asm volatile("{.reg .pred q; .reg .b32 t; shfl.sync.up.b32 t|q, %0, %1, 0, -1;\n @q add.u32 %0, %0, t;}" : "+r"(inc) : "r"(o));
            sum = inc - sum;
#pragma unroll
            for (int q = 0; q < NBW; q++) {
                const unsigned a2 = sum + u[q].x + u[q].y;
                sts128(SM_BKT + (lane * NBW + q) * 16, sum, sum + u[q].x, a2, a2 + u[q].z);
                sum = a2 + u[q].z + u[q].w;
            }
            const unsigned t0 = tstart + ((__reduce_max_sync(~0u, mx) & 0xFFF8) << 1) + T0DELTA;
            if (lane == 31) sts64(totA + 8, (inc >> 2) + bad, t0);
        } else {
            if (elect()) {
                asm volatile("prefetch.tensormap [%0];" ::"l"(&tmx) : "memory");
                asm volatile("prefetch.tensormap [%0];" ::"l"(&tmw) : "memory");
                asm volatile("prefetch.tensormap [%0];" ::"l"(&tmo) : "memory");
                const int r = cta * PFLEAD, m = min(PFLEAD, p.N - r);
#ifdef PFT
                while (clk() - tstart < PFT);
#endif
                if (m > 0) pf_l2(p.x + (size_t)r * 1024, m * 2048);
                if (cta < 128) pf_l2(p.wo + cta * 512, 1024);
#pragma unroll 1
                for (int i = 0; i < (PFD ? EPC / 64 : 0); i++) {
                    const int eb = (i * NCTA + cta) * 64, n = min(64, p.E - eb);
                    while (clk() - tstart < PF0 + i * PFD);
                    if (n > 0) { pf_l2(p.ea + (size_t)eb * 16, n * 32); pf_l2(p.sh + (size_t)eb * 4, n * 8); }
                }
            }
            put();
        }
        cta_sync();
        total = __shfl_sync(~0u, lds32(totA + 8), 0);
        slow = total > CAP;
        nst = (total + 7) >> 3;
    } else {
        {
            const unsigned du = DUM + (((cta * NCH + tid) & 31) << (18 + BSH));
#pragma unroll
            for (int k = 0; k < 3; k++) sts128(SM_STAGE + (tid + k * NXT) * 16, du, du, du, ~0u);
            if (tid < NCTA) sts32(SM_CNT + tid * 4, 0);
        }
        TK(24, e0);
        nsync<6, NXT>();
        TK(0, e0);
        const bool h2 = tid < NCTA * NCH - 2 * NXT;
        unsigned cc[3];
        const char* xo[3];
#pragma unroll
        for (int k = 0; k < 3; k++) {
            const unsigned i = tid + k * NXT;
            cc[k] = (i * 6554) >> 16;
            xo[k] = pin64((const char*)(p.xch + (cc[k] * ((NCTA - 1) * NCH) + cta * NCH + i)));
        }
        TK(26, d4.x);
        if (has) {
            const unsigned ss[4] = {s4.x, s4.y, s4.z, s4.w}, dd[4] = {d4.x, d4.y, d4.z, d4.w};
            unsigned c[4], o[4];
#pragma unroll
            for (int j = 0; j < 4; j++) { c[j] = __umulhi(dd[j], 0xFFFFFFFFu / NPC + 1); o[j] = atoms_add(SM_CNT + c[j] * 4, 0x15558); }
#pragma unroll
            for (int j = 0; j < 4; j++) {
                const unsigned dl = dd[j] - c[j] * NPC;
                sts32(SM_STAGE + (c[j] * (NCH * 4) + min(o[j] >> 16, NCH * 4 - 1)) * 4, (ss[j] << 18) + (tid * 4 + j) + dl * 2048 + (dl * 43 >> 8) * 4096);
            }
        }
        TK(28, e0);
        nsync<7, NXT + 32>();
        TK(1, e0);
        const unsigned ep = (lds32(totA) << 8) | 0x80000000u;
        {
            const unsigned tag = ep | (min((clk() - tstart) >> 4, 0x1FFFu) << 3);
            uint4 v[3];
#pragma unroll
            for (int k = 0; k < 3; k++) v[k] = lds128(SM_STAGE + (tid + k * NXT) * 16);
#pragma unroll
            for (int k = 0; k < 3; k++)
                if (k < 2 || h2) asm volatile(XST " [%0], {%1,%2,%3,%4};" ::"l"(xo[k]), "r"(v[k].x), "r"(v[k].y), "r"(v[k].z), "r"(tag + (v[k].w != ~0u)) : "memory");
        }
        narrive<10, NXT + 32>();
        TK(16, e0);
        if ((unsigned)__cvta_generic_to_shared(smem_raw) != SB) __trap();
        if (tid < NBW * 32 + 8) { const unsigned v = tid < NBW * 32 ? 0 : CAP * 4; sts128(SM_BKT + tid * 16, v, v, v, v); }
        if (tid < 384) { const unsigned v = tid < 381 ? NCONS << 23 : 0; sts128(SM_EID + tid * 16, v, v, v, v); }
        if (tid < 1392 / 4) sts128(SM_SRC + tid * 16, p.N * 4 - 4, p.N * 4 - 4, p.N * 4 - 4, p.N * 4 - 4);
        if (tid < 159) sts128(SM_BITS + tid * 16, 0, 0, 0, 0);
#pragma unroll
        for (int k = 0; k < 4; k++) {
            const unsigned pos = tid + k * (NCONS * 32), st = pos >> 3, j = pos & 7;
            dsc[k] = pin(pos | (((st % NX) * 8 + j) << 11) | ((((st % NR) * 8 + j) * (RSTR / 32)) << 21));
        }
        const char* const xi = pin64((const char*)(p.xch + cta * (NCTA * NCH) + tid));
        uint4 rc[3];
        rc[0].w = rc[1].w = 0;
        rc[2].w = h2 ? 0 : ep;
        rc[2].x = ~0u;
        nsync<8, NXT + 32>();
        TK(18, e0);
        {
            bool bad;
            int it = 0;
            do {
#pragma unroll
                for (int k = 0; k < 3; k++)
                    asm volatile("{.reg .pred q; .reg .b32 t; xor.b32 t, %3, %5; setp.gt.u32 q, t, 0xFFFF;\n @q ld.relaxed.gpu.global.v4.u32 {%0,%1,%2,%3}, [%4];}"
                                 : "+r"(rc[k].x), "+r"(rc[k].y), "+r"(rc[k].z), "+r"(rc[k].w) : "l"(xi + k * (NXT * 16)), "r"(ep) : "memory");
                bad = ((rc[0].w ^ ep) | (rc[1].w ^ ep) | (rc[2].w ^ ep)) > 0xFFFF;
            } while (__any_sync(~0u, bad) && ++it < 4096);
            if (bad || ((rc[0].w | rc[1].w | rc[2].w) & 1)) {
                rc[0].x = rc[1].x = rc[2].x = ~0u;
                sts32(totA + 4, CAP + 1);
            }
#ifdef DBG_TIMES
            if (tid == 0) sts32(totA + 20, it * 2);
#endif
        }
        TK(2, e0);
        unsigned ord[3][3], ba[3][3], ve[3][3], vs[3][3];
#pragma unroll
        for (int k = 0; k < 3; k++) {
            const unsigned rr[3] = {rc[k].x, rc[k].y, rc[k].z};
            if (rr[0] < DUM) {
#pragma unroll
                for (int j = 0; j < 3; j++) { ba[k][j] = pin((rr[j] >> (18 + BSH)) * 4); ord[k][j] = atoms_add(SM_BKT + ba[k][j], 4); }
            }
        }
        sts32(SM_CNT + warp * 4, __reduce_max_sync(~0u, max(rc[0].w, max(rc[1].w, rc[2].w))));
        narrive<9, NXT + 32>();
        TK(15, e0);
#pragma unroll
        for (int k = 0; k < 3; k++) {
            const unsigned rr[3] = {rc[k].x, rc[k].y, rc[k].z};
#pragma unroll
            for (int j = 0; j < 3; j++) { ve[k][j] = pin(rr[j] * 512 + cc[k] * (EPC * 4) - (rr[j] & 0x7FF) * 508); vs[k][j] = pin((rr[j] >> 16) & 0xFFFC); }
        }
        cta_sync();
        TK(19, e0);
        total = __shfl_sync(~0u, lds32(totA + 8), 0);
        T0 = lds32(totA + 12);
#pragma unroll
        for (int k = 0; k < 3; k++) {
            if (rc[k].x < DUM) {
                unsigned ps[3];
#pragma unroll
                for (int j = 0; j < 3; j++) ps[j] = ord[k][j] + lds32(SM_BKT + ba[k][j]);
#pragma unroll
                for (int j = 0; j < 3; j++)
                    asm volatile("{.reg .pred q; setp.lt.u32 q, %0, " STR(CAP) "*4;\n @q st.shared.u32 [%0+" STR(SM_EID) "], %1;\n @q st.shared.u32 [%0+" STR(SM_SRC) "], %2;}"
                                 ::"r"(ps[j]), "r"(ve[k][j]), "r"(vs[k][j]) : "memory");
            }
        }
        slow = total > CAP;
        nst = (total + 7) >> 3;
        const unsigned lim = (nst % NX) << 14;
#pragma unroll
        for (int k = 0; k < 4; k++) dsc[k] = pin(dsc[k] - lim + ((dsc[k] & 0x3C000) >= lim ? 0 : NX << 14));
        TK(20, e0);
#ifdef DBG_TIMES
        if (tid == 0) { sts128(SM_NEXT + CAPP * 4, tk0, tk1, tk24, tk26); sts128(SM_NEXT + CAPP * 4 + 16, tk28, tk16, tk2, tk15); sts128(SM_NEXT + CAPP * 4 + 32, tk19, tk20, tk18, tstart); }
#endif
    }

    int wid = warp;
    if (slow) {
        asm volatile("fence.mbarrier_init.release.cluster;" ::: "memory");
        fence_async();
        cta_sync();
        if (tid < 4) { bar_expect(wbar + tid * 8, 16384); tma_2d(SB + tid * 16384, &tmw, wbar + tid * 8, tid * 64, 0); }
        slow_path(p);
    } else if (warp < NCONS) {
        cta_sync();
        TK(3, tid);
        unsigned q[4], a[4];
        const bool k3 = warp * 32 + 3 * NCONS * 32 < total;
#pragma unroll
        for (int k = 0; k < 4; k++) if (k < 3 || k3) q[k] = lds32(SM_EID + tid * 4 + k * (NCONS * 128));
#pragma unroll
        for (int k = 0; k < 4; k++) if (k < 3 || k3) {
            a[k] = ((q[k] >> 23) & 15) * (BW * 4) + warp * 4;
            asm volatile("red.shared.or.b32 [%0], %1;" ::"r"(SM_BITS + k * (NCONS * 4) + a[k]), "r"(1u << lane) : "memory");
        }
        __syncwarp();
#pragma unroll
        for (int k = 0; k < 4; k++) if (k < 3 || k3) a[k] = lds32(SM_BITS + k * (NCONS * 4) + a[k]);
#pragma unroll
        for (int k = 0; k < 4; k++) if (k < 3 || k3)
            sts32(SM_NEXT + k * (NCONS * 128) + ((warp * 32) | ((lane + 31 - __clz(__funnelshift_r(a[k], a[k], lane))) & 31)) * 4, dsc[k] | ((q[k] >> 2) & 0x1C0000));
        asm volatile("bar.sync 5, %0;" ::"n"(NCONS * 32) : "memory");
        TK(21, tid);
        unsigned head;
        {
            const unsigned c = 31 - lane, m0 = lds32(SM_BITS + warp * (BW * 4) + c * 4), m1 = lds32(SM_BITS + warp * (BW * 4) + 128 + min(c, 12) * 4);
            const unsigned l0 = m0 ? c * 32 + 31 - __clz(m0) : CAPP - 1, l1 = m1 ? c * 32 + 1055 - __clz(m1) : CAPP - 1;
            const unsigned f0 = lds32(SM_NEXT + l0 * 4), f1 = lane ? lds32(SM_NEXT + l1 * 4) : 0x1C0000 | (warp << 21);
            const unsigned b0 = __ballot_sync(~0u, m0), b1 = __ballot_sync(~0u, m1) | 1, lt = (1u << lane) - 1;
            const unsigned h1 = __shfl_sync(~0u, f1, 31 - __clz(b1)), n1 = __shfl_sync(~0u, f1, 31 - __clz(b1 & lt));
            const unsigned h0 = __shfl_sync(~0u, f0, 31 - __clz(b0)), n0 = __shfl_sync(~0u, f0, 31 - __clz(b0 & lt));
            sts32(SM_NEXT + l0 * 4, b0 & lt ? n0 : h1);
            sts32(SM_NEXT + l1 * 4, n1);
            head = b0 ? h0 : h1;
            __syncwarp();
        }
        TK(22, tid);
#ifdef DBG_TIMES
        if (tid == 0) sts128(SM_NEXT + CAPP * 4 + 48, tk3, tk21, tk22, 0);
#endif
        wid = consumer(head);
        STAMPL(4);
    } else if (warp == NCONS) {
        cta_sync();
        const unsigned late = issuer(&tmx, p, nst, T0);
        wid = NCONS;
#pragma unroll 1
        for (int i = 0; i < 4; i++) {
            bwait(SM_EMPTY + (nst + i - NX) * 8);
            if (elect()) { bar_expect(wbar + i * 8, 16384); tma_2d(SB + i * 16384, &tmw, wbar + i * 8, i * 64, 0); }
        }
#ifdef DBG_TR
        for (int i = lane; i < nst; i += 32) g_trace[(cta * 180 + i) * 4 + 3] = lds32(SM_TR + i * 8) - T0;
#endif
#ifdef DBG_TIMES
        if (lane < 15) { const unsigned ix[15] = {0, 1, 24, 26, 28, 16, 2, 15, 19, 20, 18, 31, 3, 21, 22}; unsigned j = 0;
#pragma unroll
            for (int q = 0; q < 15; q++) j = lane == q ? ix[q] : j;
            const unsigned v = lds32(SM_NEXT + CAPP * 4 + lane * 4); g_times[cta * 32 + j] = j == 31 ? v & ~1 : v | 1; }
        STAMPW(13, lds32(totA + 16)); STAMPW(17, lds32(totA + 20));
#endif
#ifdef DBG_H
        STAMPW(8, late & ~1); STAMPW(7, (T0 - tstart) & ~1); STAMPW(14, nst & ~1); STAMPW(9, T0 & ~1);
#endif
        cta_sync();
    } else {
        const unsigned ewait = recorder(p, __shfl_sync(~0u, (tid >> 5) & 1, 0), nst, cg0, cg1);
        wid = NCONS + 1 + ((ewait >> 3) & 1);
#ifdef DBG_R
        if (wid == 15) STAMPW(12, ewait); else STAMPW(11, ewait);
#endif
        cta_sync();
    }

    wid = __shfl_sync(~0u, wid, 0);
    const int wg = wid >> 2, wq = wid & 3;
    int ln;
    asm volatile("mov.u32 %0, %%laneid;" : "=r"(ln));
    const bool lead = wq == 0 && ln == 0;
    unsigned af[16][4];
    const unsigned wt = SB + wg * 16384;
    const unsigned wa = wt + (((ln >> 4) * 8 + (ln & 7)) << 7) + (((2 * wq + ((ln >> 3) & 1)) ^ (ln & 7)) << 4);
    bwait(wbar + wg * 8);
#pragma unroll
    for (int k = 0; k < 8; k++) ldsm4t(af[k], wa + k * 2048);
    fence_async();
    cta_sync();
    STAMPL(5);
    if (lead) { bar_expect(wbar + 32 + wg * 8, 16384); tma_2d(wt, &tmw, wbar + 32 + wg * 8, wg * 64, 128); }
    const uint64_t desc0 = (uint64_t)(((SM_H) >> 4) & 0x3FFF) | (1ull << 16) | (64ull << 32) | (1ull << 62);
    float d[32];
    const int row0 = cta * (NPC * 4);
    wg_fence();
#pragma unroll
    for (int k = 0; k < 8; k++) wgmma_rs<64>(d, af[k], desc0 + (k >> 2) * (HPANEL >> 4) + (k & 3) * 2, k != 0);
    wg_commit();
    bwait(wbar + 32 + wg * 8);
#pragma unroll
    for (int k = 0; k < 8; k++) ldsm4t(af[8 + k], wa + k * 2048);
    wg_fence();
#pragma unroll
    for (int k = 8; k < 16; k++) wgmma_rs<64>(d, af[k], desc0 + (k >> 2) * (HPANEL >> 4) + (k & 3) * 2, 1);
    wg_commit();
    wg_wait0();
    out_chunk<64>(d, wt, &tmo, wg, row0, true, wa, lead);
#pragma unroll 1
    for (int c = 1; c < 4; c++) {
        wg_fence();
#pragma unroll
        for (int k = 0; k < 16; k++) wgmma_rs<64>(d, af[k], desc0 + c * 512 + (k >> 2) * (HPANEL >> 4) + (k & 3) * 2, k != 0);
        wg_commit();
        wg_wait0();
        out_chunk<64>(d, wt, &tmo, wg, row0 + c * 64, false, wa, lead);
    }
    wg_fence();
#pragma unroll
    for (int k = 0; k < 16; k++) wgmma_rs<48>(d, af[k], desc0 + 4 * 512 + (k >> 2) * (HPANEL >> 4) + (k & 3) * 2, k != 0);
    wg_commit();
    wg_wait0();
    out_chunk<48>(d, wt, &tmo, wg, row0 + 256, false, wa, lead);
    if (lead) asm volatile("cp.async.bulk.wait_group.read 0;" ::: "memory");
    STAMPL(6);
#ifdef DBG_GT
    { unsigned g; asm volatile("mov.u32 %0, %%globaltimer_lo;" : "=r"(g)); STAMPW(30, g & ~1); }
#endif
}

typedef CUresult (*EncFn)(CUtensorMap*, CUtensorMapDataType, cuuint32_t, void*, const cuuint64_t*, const cuuint64_t*, const cuuint32_t*,
                          const cuuint32_t*, CUtensorMapInterleave, CUtensorMapSwizzle, CUtensorMapL2promotion, CUtensorMapFloatOOBfill);

extern "C" void kernel_launch(void* const* d_in, const int* in_sizes, int n_in, void* d_out, int out_size) {
    static EncFn enc = nullptr;
    static int nsm = 0;
    static void* xch = nullptr;
    if (!enc) {
        void* fn = nullptr; cudaDriverEntryPointQueryResult qr;
        cudaGetDriverEntryPoint("cuTensorMapEncodeTiled", &fn, cudaEnableDefault, &qr);
        enc = (EncFn)fn;
        cudaGetSymbolAddress(&xch, g_xch);
        int dev = 0; cudaGetDevice(&dev);
        cudaDeviceGetAttribute(&nsm, cudaDevAttrMultiProcessorCount, dev);
        cudaFuncSetAttribute(mace_kernel, cudaFuncAttributeMaxDynamicSharedMemorySize, SM_TOTAL);
    }
    Params p;
    p.x = (const __nv_bfloat16*)d_in[0]; p.src = (const int*)d_in[1]; p.dst = (const int*)d_in[2];
    p.sh = (const __nv_bfloat16*)d_in[3]; p.ea = (const __nv_bfloat16*)d_in[4]; p.cg = (const __nv_bfloat16*)d_in[5];
    p.wr = (const __nv_bfloat16*)d_in[6]; p.wo = (const __nv_bfloat16*)d_in[7];
    p.N = in_sizes[0] / 1024; p.E = in_sizes[1];
    p.Ef = (nsm >= NCTA && p.N <= NCTA * NPC && p.E <= NCTA * EPC && p.N > 1 && (p.E & 3) == 0) ? p.E : 0;
    p.xch = (uint4*)xch;
    p.rate = (unsigned)((double)PACE * ((double)p.E / 160000.0) * 256.0 / (double)p.N);
    p.zero = 0;
    CUtensorMap tmx, tmw, tmo;
    const cuuint32_t es[3] = {1, 1, 1};
    {
        cuuint64_t dims[3] = {64, (cuuint64_t)p.N * 4, 4}; cuuint64_t str[2] = {512, 128}; cuuint32_t box[3] = {64, 4, 4};
        enc(&tmx, CU_TENSOR_MAP_DATA_TYPE_BFLOAT16, 3, d_in[0], dims, str, box, es, CU_TENSOR_MAP_INTERLEAVE_NONE, CU_TENSOR_MAP_SWIZZLE_128B, CU_TENSOR_MAP_L2_PROMOTION_NONE, CU_TENSOR_MAP_FLOAT_OOB_FILL_NONE);
    }
    {
        cuuint64_t dims[2] = {256, 256}; cuuint64_t str[1] = {512}; cuuint32_t box[2] = {64, 128};
        enc(&tmw, CU_TENSOR_MAP_DATA_TYPE_BFLOAT16, 2, d_in[7], dims, str, box, es, CU_TENSOR_MAP_INTERLEAVE_NONE, CU_TENSOR_MAP_SWIZZLE_128B, CU_TENSOR_MAP_L2_PROMOTION_NONE, CU_TENSOR_MAP_FLOAT_OOB_FILL_NONE);
    }
    {
        cuuint64_t dims[2] = {256, (cuuint64_t)p.N * 4}; cuuint64_t str[1] = {512}; cuuint32_t box[2] = {64, 16};
        enc(&tmo, CU_TENSOR_MAP_DATA_TYPE_BFLOAT16, 2, d_out, dims, str, box, es, CU_TENSOR_MAP_INTERLEAVE_NONE, CU_TENSOR_MAP_SWIZZLE_128B, CU_TENSOR_MAP_L2_PROMOTION_NONE, CU_TENSOR_MAP_FLOAT_OOB_FILL_NONE);
    }
    const int grid = p.Ef ? NCTA : (p.N + NPC - 1) / NPC;
    mace_kernel<<<grid, 512, SM_TOTAL>>>(p, tmx, tmw, tmo);
}
```

```cpp
#include <cuda_runtime.h>
#include <cuda_bf16.h>
#include <cuda.h>
#include <stdint.h>

#ifndef NX
#define NX 10
#endif
#ifndef NR
#define NR 9
#endif
#ifndef PACE
#define PACE 50000
#endif
#ifndef T0DELTA
#define T0DELTA 5200
#endif
#ifndef BSH
#define BSH 5
#endif
#ifndef POLLT
#define POLLT 2900
#endif
#ifndef PF0
#define PF0 1000
#endif
#ifndef PFD
#define PFD 0
#endif
#ifndef PFLEAD
#define PFLEAD 8
#endif
#ifndef RSPL
#define RSPL 10
#endif
#ifndef RLDG
#define RLDG "ld.global.nc"
#endif
#ifndef DISP
#define DISP 1
#endif
#ifndef XST
#define XST "st.relaxed.gpu.global.v4.u32"
#endif
#define NCTA 132
#define NPC 76
#define EPC 1216
#define NCH 10
#define CAP 1376
#define CAPP 1440
#define NCONS 13
#define RSTR 608
#define NBW ((((NCTA * NPC) >> BSH) + 128) / 128)

#define SB 1024
#define SM_X SB
#define SM_R (SM_X + NX * 16384)
#define SM_EID (SM_R + NR * 8 * RSTR)
#define SM_NEXT (SM_EID + 6144)
#define SM_H (SB + 65536)
#define HPANEL 38912
#define SM_FULL (SM_H + 4 * HPANEL)
#define SM_EMPTY (SM_FULL + CAPP + 128)
#define SM_SRC (SM_EMPTY + CAPP)
#define SM_BITS (SM_SRC + 1392 * 4)
#define SM_MISC (SM_BITS + 2544)
#define SM_TOTAL (SM_MISC + 128 - SB)
#define NXT 448
#define SM_STAGE SM_R
#define SM_CNT (SM_R + NXT * 48)
#define SM_WR (SM_CNT + 640)
#define SM_BKT (SM_WR + 16 * 528)
static_assert(SM_BKT + NBW * 512 + 128 <= SM_EID, "smem");
#define DUM ((unsigned)(NBW * 128) << (18 + BSH))
#define BW 45
static_assert(SM_NEXT + CAPP * 4 <= SM_FULL && SM_TOTAL <= 232448, "smem");
#define STR_(x) #x
#define STR(x) STR_(x)

__device__ uint4 g_xch[NCTA * NCTA * NCH + 8];
#ifdef DBG_TIMES
extern "C" { __device__ unsigned g_times[NCTA * 32]; }
#define STAMPV(m, i, v) asm volatile("{.reg .pred q; .reg .b32 t; .reg .b64 a, b; mov.u32 t, %%tid.x; and.b32 t, t, %0; setp.eq.u32 q, t, 0; mov.u32 t, %%ctaid.x; mov.u64 b, g_times; mad.wide.u32 a, t, 128, b; @q st.global.u32 [a+%1], %2;}" ::"n"(m), "n"((i) * 4), "r"(v) : "memory")
#define STAMP(i) STAMPV(1023, i, clk() | 0x1)
#define STAMPS(i, v) sts32(SM_BITS + (i) * 4, v)
#define STAMPL(i) if (wid == 0) STAMPS(i, clk() | 0x1)
#define STAMPW(i, v) asm volatile("{.reg .b32 t; .reg .b64 a, b; mov.u32 t, %%ctaid.x; mov.u64 b, g_times; mad.wide.u32 a, t, 128, b; st.global.u32 [a+%0], %1;}" ::"n"((i) * 4), "r"(v) : "memory")
#define TK(i, dep) unsigned tk##i; asm volatile("{.reg .b32 t; and.b32 t, %1, %2; mov.u32 %0, %%clock; add.u32 %0, %0, t;}" : "=r"(tk##i) : "r"(dep), "r"(p.zero) : "memory")
#define TKO(i) STAMPV(1023, i, tk##i | 1)
#ifndef DBG_PRO
#undef TK
#define TK(i, dep)
#endif
#else
#define STAMP(i)
#define STAMPL(i)
#define STAMPS(i, v)
#define STAMPV(m, i, v)
#define STAMPW(i, v)
#define TK(i, dep)
#define TKO(i)
#endif

struct Params {
    const int* src; const int* dst; uint4* xch; const __nv_bfloat16* wr;
    int Ef, N;
    const __nv_bfloat16* cg; const __nv_bfloat16* x; const __nv_bfloat16* sh; const __nv_bfloat16* ea; const __nv_bfloat16* wo;
    int E; unsigned rate, zero;
};

__device__ __forceinline__ unsigned clk() { unsigned c; asm volatile("mov.u32 %0, %%clock;" : "=r"(c)); return c; }
__device__ __forceinline__ bool elect() { unsigned p; asm volatile("{.reg .pred P; elect.sync _|P, 0xffffffff; selp.u32 %0,1,0,P;}" : "=r"(p)); return p; }
__device__ __forceinline__ bool try_wait(unsigned a) { unsigned ok; asm volatile("{.reg .pred p; mbarrier.try_wait.parity.shared::cta.b64 p,[%1],0; selp.u32 %0,1,0,p;}" : "=r"(ok) : "r"(a) : "memory"); return ok; }
__device__ __forceinline__ void bwait(unsigned a) { if (!try_wait(a)) { for (int i = 0; i < (1 << 18) && !try_wait(a); i++); } }
__device__ __forceinline__ unsigned pin(unsigned x) { unsigned y; asm volatile("mov.u32 %0, %1;" : "=r"(y) : "r"(x)); return y; }
__device__ __forceinline__ const char* pin64(const char* x) { const char* y; asm volatile("mov.u64 %0, %1;" : "=l"(y) : "l"(x)); return y; }
__device__ __forceinline__ void split(unsigned x, unsigned c) { asm volatile("{.reg .pred p; setp.eq.u32 p, %0, %1; @p exit;}" ::"r"(x), "r"(c) : "memory"); }
__device__ __forceinline__ void bar_init(unsigned a, unsigned c) { asm volatile("mbarrier.init.shared::cta.b64 [%0], %1;" ::"r"(a), "r"(c) : "memory"); }
__device__ __forceinline__ void bar_expect(unsigned a, unsigned bytes) { asm volatile("mbarrier.arrive.expect_tx.shared::cta.b64 _, [%0], %1;" ::"r"(a), "r"(bytes) : "memory"); }
__device__ __forceinline__ void bar_complete(unsigned a, unsigned bytes) { asm volatile("mbarrier.complete_tx.relaxed.cta.shared::cta.b64 [%0], %1;" ::"r"(a), "r"(bytes) : "memory"); }
__device__ __forceinline__ void fence_async() { asm volatile("fence.proxy.async.shared::cta;" ::: "memory"); }
template <int ID, int N> __device__ __forceinline__ void nsync() { asm volatile("bar.sync %0, %1;" ::"n"(ID), "n"(N) : "memory"); }
template <int ID, int N> __device__ __forceinline__ void narrive() { asm volatile("bar.arrive %0, %1;" ::"n"(ID), "n"(N) : "memory"); }
__device__ __forceinline__ void cta_sync() { asm volatile("bar.sync 0, 512;" ::: "memory"); }
__device__ __forceinline__ unsigned lds32(unsigned a) { unsigned v; asm volatile("ld.shared.u32 %0,[%1];" : "=r"(v) : "r"(a) : "memory"); return v; }
__device__ __forceinline__ unsigned lds16(unsigned a) { unsigned v; asm volatile("ld.shared.u16 %0,[%1];" : "=r"(v) : "r"(a) : "memory"); return v; }
__device__ __forceinline__ uint4 lds128(unsigned a) { uint4 v; asm volatile("ld.shared.v4.u32 {%0,%1,%2,%3},[%4];" : "=r"(v.x), "=r"(v.y), "=r"(v.z), "=r"(v.w) : "r"(a) : "memory"); return v; }
__device__ __forceinline__ void sts32(unsigned a, unsigned v) { asm volatile("st.shared.u32 [%0],%1;" ::"r"(a), "r"(v) : "memory"); }
__device__ __forceinline__ void sts16(unsigned a, unsigned v) { asm volatile("st.shared.u16 [%0],%1;" ::"r"(a), "r"(v) : "memory"); }
__device__ __forceinline__ void sts64(unsigned a, unsigned x, unsigned y) { asm volatile("st.shared.v2.u32 [%0],{%1,%2};" ::"r"(a), "r"(x), "r"(y) : "memory"); }
__device__ __forceinline__ void sts128(unsigned a, unsigned x, unsigned y, unsigned z, unsigned w) { asm volatile("st.shared.v4.u32 [%0],{%1,%2,%3,%4};" ::"r"(a), "r"(x), "r"(y), "r"(z), "r"(w) : "memory"); }
__device__ __forceinline__ unsigned atoms_add(unsigned a, unsigned v) { unsigned o; asm volatile("atom.shared.add.u32 %0,[%1],%2;" : "=r"(o) : "r"(a), "r"(v) : "memory"); return o; }
__device__ __forceinline__ void ldsm4t(unsigned* r, unsigned a) { asm volatile("ldmatrix.sync.aligned.m8n8.x4.trans.shared.b16 {%0,%1,%2,%3},[%4];" : "=r"(r[0]), "=r"(r[1]), "=r"(r[2]), "=r"(r[3]) : "r"(a) : "memory"); }
__device__ __forceinline__ void stsm4t(unsigned a, unsigned r0, unsigned r1, unsigned r2, unsigned r3) { asm volatile("stmatrix.sync.aligned.m8n8.x4.trans.shared.b16 [%0],{%1,%2,%3,%4};" ::"r"(a), "r"(r0), "r"(r1), "r"(r2), "r"(r3) : "memory"); }
__device__ __forceinline__ unsigned pack2(float lo, float hi) { unsigned p; asm("cvt.rn.bf16x2.f32 %0,%1,%2;" : "=r"(p) : "f"(hi), "f"(lo)); return p; }
__device__ __forceinline__ void mma1688(float* d, unsigned a0, unsigned a1, unsigned b0) {
    asm("mma.sync.aligned.m16n8k8.row.col.f32.bf16.bf16.f32 {%0,%1,%2,%3},{%4,%5},{%6},{%7,%7,%7,%7};"
        : "=f"(d[0]), "=f"(d[1]), "=f"(d[2]), "=f"(d[3]) : "r"(a0), "r"(a1), "r"(b0), "f"(0.f));
}
__device__ __forceinline__ void mma16816(float* d, const unsigned* a, unsigned b0, unsigned b1) {
    asm volatile("mma.sync.aligned.m16n8k16.row.col.f32.bf16.bf16.f32 {%0,%1,%2,%3},{%4,%5,%6,%7},{%8,%9},{%10,%10,%10,%10};"
        : "=f"(d[0]), "=f"(d[1]), "=f"(d[2]), "=f"(d[3]) : "r"(a[0]), "r"(a[1]), "r"(a[2]), "r"(a[3]), "r"(b0), "r"(b1), "f"(0.f));
}
__device__ __forceinline__ void tma_x(unsigned da, const void* tm, unsigned ba, int c1) {
    asm volatile("cp.async.bulk.tensor.3d.shared::cluster.global.mbarrier::complete_tx::bytes [%0], [%1, {%3,%4,%3}], [%2];" ::"r"(da), "l"(tm), "r"(ba), "r"(0), "r"(c1) : "memory");
}
__device__ __forceinline__ void tma_2d(unsigned da, const CUtensorMap* tm, unsigned ba, int c0, int c1) {
    asm volatile("cp.async.bulk.tensor.2d.shared::cluster.global.mbarrier::complete_tx::bytes [%0], [%1, {%3,%4}], [%2];" ::"r"(da), "l"(tm), "r"(ba), "r"(c0), "r"(c1) : "memory");
}
__device__ __forceinline__ void tma_st(const CUtensorMap* tm, unsigned sa, int c0, int c1) {
    asm volatile("cp.async.bulk.tensor.2d.global.shared::cta.bulk_group [%0, {%2,%3}], [%1];" ::"l"(tm), "r"(sa), "r"(c0), "r"(c1) : "memory");
}
__device__ __forceinline__ void pf_l2(const void* p, unsigned bytes) { asm volatile("cp.async.bulk.prefetch.L2.global [%0], %1;" ::"l"(p), "r"(bytes) : "memory"); }

#define WG_REGS24(d) "+f"(d[0]), "+f"(d[1]), "+f"(d[2]), "+f"(d[3]), "+f"(d[4]), "+f"(d[5]), "+f"(d[6]), "+f"(d[7]), \
    "+f"(d[8]), "+f"(d[9]), "+f"(d[10]), "+f"(d[11]), "+f"(d[12]), "+f"(d[13]), "+f"(d[14]), "+f"(d[15]), \
    "+f"(d[16]), "+f"(d[17]), "+f"(d[18]), "+f"(d[19]), "+f"(d[20]), "+f"(d[21]), "+f"(d[22]), "+f"(d[23])
template <int NN> __device__ __forceinline__ void wgmma_rs(float* d, const unsigned* a, uint64_t desc, int scale_d);
template <> __device__ __forceinline__ void wgmma_rs<48>(float* d, const unsigned* a, uint64_t desc, int scale_d) {
    asm volatile("{.reg .pred p; setp.ne.b32 p, %29, 0;\n"
        "wgmma.mma_async.sync.aligned.m64n48k16.f32.bf16.bf16 {%0,%1,%2,%3,%4,%5,%6,%7,%8,%9,%10,%11,%12,%13,%14,%15,%16,%17,%18,%19,"
        "%20,%21,%22,%23}, {%24,%25,%26,%27}, %28, p, 1, 1, 0;}"
        : WG_REGS24(d)
        : "r"(a[0]), "r"(a[1]), "r"(a[2]), "r"(a[3]), "l"(desc), "r"(scale_d));
}
template <> __device__ __forceinline__ void wgmma_rs<64>(float* d, const unsigned* a, uint64_t desc, int scale_d) {
    asm volatile("{.reg .pred p; setp.ne.b32 p, %37, 0;\n"
        "wgmma.mma_async.sync.aligned.m64n64k16.f32.bf16.bf16 {%0,%1,%2,%3,%4,%5,%6,%7,%8,%9,%10,%11,%12,%13,%14,%15,%16,%17,%18,%19,"
        "%20,%21,%22,%23,%24,%25,%26,%27,%28,%29,%30,%31}, {%32,%33,%34,%35}, %36, p, 1, 1, 0;}"
        : WG_REGS24(d), "+f"(d[24]), "+f"(d[25]), "+f"(d[26]), "+f"(d[27]), "+f"(d[28]), "+f"(d[29]), "+f"(d[30]), "+f"(d[31])
        : "r"(a[0]), "r"(a[1]), "r"(a[2]), "r"(a[3]), "l"(desc), "r"(scale_d));
}
__device__ __forceinline__ void wg_fence() { asm volatile("wgmma.fence.sync.aligned;" ::: "memory"); }
__device__ __forceinline__ void wg_commit() { asm volatile("wgmma.commit_group.sync.aligned;" ::: "memory"); }
__device__ __forceinline__ void wg_wait0() { asm volatile("wgmma.wait_group.sync.aligned 0;" ::: "memory"); }

#define PF(D, RW, K, J0, J1) \
    "cvt.rn.bf16x2.f32 t0, " #D "1, " #D "0;\n cvt.rn.bf16x2.f32 t1, " #D "3, " #D "2;\n" \
    "mov.b32 {lo, hi}, " #RW ";\n mov.b32 u0, {lo, lo};\n mov.b32 u1, {hi, hi};\n" \
    "fma.rn.bf16x2 a" #K "_" #J0 ", t0, u0, a" #K "_" #J0 ";\n fma.rn.bf16x2 a" #K "_" #J1 ", t1, u1, a" #K "_" #J1 ";\n"
#define MMA(D, A0, A1) "mma.sync.aligned.m16n8k8.row.col.f32.bf16.bf16.f32 {" #D "0," #D "1," #D "2," #D "3}, {" #A0 "," #A1 "}, {bf}, {fz,fz,fz,fz};\n"
#define LDX(X, OFF) "ldmatrix.sync.aligned.m8n8.x4.trans.shared.b16 {" #X "0," #X "1," #X "2," #X "3}, [xa+" STR(SM_X) "+" #OFF "];\n"
#define DECODE \
    "lop3.b32 xa, dn, 0x3F800, %1, 0xEA;\n" \
    "shr.u32 t2, dn, 21;\n mad.lo.u32 ra, t2, 32, %2;\n mad.lo.u32 ca, t2, 32, %3;\n" \
    "and.b32 t3, dn, 0x7FF;\n shl.b32 t3, t3, 2;\n" SETD
#define LOADS \
    LDX(x, 0) "@act ld.shared.u32 bf, [ca+" STR(SM_R) "];\n" LDX(y, 512) LDR(r, 0) \
    "ld.shared.u32 dn, [t3+" STR(SM_NEXT) "];\n"
#if DISP == 0
#define SETD "bfe.u32 ix, dn, 18, 3;\n"
#define DISPATCH "brx.idx.uni ix, TS;\n"
#define T23
#define T45
#else
#define SETD "and.b32 ix, dn, 0x40000;\n setp.ne.u32 q0, ix, 0;\n and.b32 ix, dn, 0x80000;\n setp.ne.u32 q1, ix, 0;\n and.b32 ix, dn, 0x100000;\n setp.ne.u32 q2, ix, 0;\n"
#define DISPATCH "@q2 bra.uni T45;\n @q1 bra.uni T23;\n @q0 bra.uni B1;\n bra.uni B0;\n"
#define T23 "T23:\n @q0 bra.uni B3;\n"
#define T45 "T45:\n @q1 bra.uni FIN;\n @q0 bra.uni B5;\n"
#endif
#define LDR(R, OFF) "ld.shared.v4.u32 {" #R "0," #R "1," #R "2," #R "3}, [ra+" STR(SM_R) "+" #OFF "];\n"
#ifdef JG
#define JIG "and.b32 t0, t0, 0xFFFF;\n"
#else
#define JIG
#endif
#define BODY(K) "B" #K ":\n" \
    MMA(d, x0, x1) MMA(e, x2, x3) LDX(x, 1024) "and.b32 bn, dn, 0x7F8;\n" \
    "mbarrier.test_wait.parity.shared::cta.b64 p, [bn+" STR(SM_FULL) "], 0;\n" \
    PF(d, r0, K, 0, 1) MMA(d, y0, y1) PF(e, r1, K, 2, 3) MMA(e, y2, y3) LDX(y, 1536) LDR(s, 128) \
    PF(d, r2, K, 4, 5) MMA(d, x0, x1) PF(e, r3, K, 6, 7) MMA(e, x2, x3) \
    PF(d, s0, K, 8, 9) MMA(d, y0, y1) \
    "@l0 mbarrier.arrive.shared::cta.b64 _, [bc+" STR(SM_EMPTY) "];\n" \
    PF(e, s1, K, 10, 11) MMA(e, y2, y3) \
    "mov.u32 bc, bn;\n" DECODE \
    "@!p bra.uni W" #K ";\n" \
    "R" #K ":\n" LOADS \
    PF(d, s2, K, 12, 13) PF(e, s3, K, 14, 15) DISPATCH
#ifdef DBG_TR
#define SM_TR (SM_NEXT + CAPP * 4)
#define TRC "mov.u32 t1, %%clock;\n st.shared.u32 [bc+" STR(SM_TR) "], t1;\n"
extern "C" { __device__ unsigned g_trace[NCTA * 4 * 180]; }
#else
#define TRC
#endif
#define WAIT(K) "W" #K ":\n mov.u32 t0, 0;\n" \
    "V" #K ":\n mbarrier.try_wait.parity.shared::cta.b64 p, [bc+" STR(SM_FULL) "], 0;\n" TRC "@p bra.uni R" #K ";\n" \
    "add.u32 t0, t0, 1;\n setp.lt.u32 p, t0, 400000;\n @p bra.uni V" #K ";\n bra.uni R" #K ";\n"
#define Z4(K, A, B, C, D) "mov.u32 a" #K "_" #A ", 0; mov.u32 a" #K "_" #B ", 0; mov.u32 a" #K "_" #C ", 0; mov.u32 a" #K "_" #D ", 0;\n"
#define ZACC(K) Z4(K, 0, 1, 2, 3) Z4(K, 4, 5, 6, 7) Z4(K, 8, 9, 10, 11) Z4(K, 12, 13, 14, 15)
#define ST4(K, A, B, C, D, R, P) "stmatrix.sync.aligned.m8n8.x4.trans.shared.b16 [" #R "+" STR(SM_H) "+" #K "*512+" #P "*" STR(HPANEL) "], {a" #K "_" #A ",a" #K "_" #B ",a" #K "_" #C ",a" #K "_" #D "};\n"
#define STH(K, R0, R1) ST4(K, 0, 1, 2, 3, R0, 0) ST4(K, 4, 5, 6, 7, R1, 1) ST4(K, 8, 9, 10, 11, R0, 2) ST4(K, 12, 13, 14, 15, R1, 3)
__device__ __forceinline__ unsigned consumer(unsigned head) {
    const int lane = threadIdx.x & 31, g = lane >> 2, t = lane & 3;
    const unsigned xl = (lane & 3) * 128 + ((((lane >> 3) + (lane & 4)) ^ (lane & 3)) << 4);
    const unsigned rl = (t >> 1) * 320 + g * 16;
    const unsigned cl = (t >> 1) == (g >> 2) ? 256 + (2 * (g & 3) + (t & 1)) * 4 : 0;
    asm volatile("{\n"
        ".reg .b32 a0_<16>, a1_<16>, a2_<16>, a3_<16>, a4_<16>, a5_<16>;\n"
        ".reg .b32 x<4>, y<4>, r<4>, s<4>, t<4>, u<2>, bf, xa, ra, ca, bn, bc, dn, ix;\n"
        ".reg .f32 d<4>, e<4>, fz;\n .reg .b16 lo, hi;\n .reg .pred p, q<3>, act, l0;\n"
#if DISP == 0
        "TS: .branchtargets B0, B1, B2, B3, B4, B5, FIN, FIN;\n"
#endif
        "mov.f32 fz, 0f00000000;\n mov.u32 bf, 0;\n setp.ne.u32 act, %3, 0;\n setp.eq.u32 l0, %1, 0;\n mov.u32 dn, %0;\n"
        ZACC(0) ZACC(1) ZACC(2) ZACC(3) ZACC(4) ZACC(5)
        "and.b32 bc, dn, 0x7F8;\n"
        DECODE "and.b32 t0, dn, 0x1C0000;\n setp.eq.u32 p, t0, 0x1C0000;\n @p bra.uni FIN;\n"
        WAIT(6)
        "R6:\n" LOADS DISPATCH
        BODY(0) BODY(1) T23 BODY(2) BODY(3) T45 BODY(4) BODY(5)
        WAIT(0) WAIT(1) WAIT(2) WAIT(3) WAIT(4) WAIT(5)
        "FIN:\n bar.sync 5, 416;\n"
#ifdef DBG_TIMES
        "mov.u32 t0, %%clock;\n or.b32 t0, t0, 1;\n mov.u32 t1, " STR(SM_BITS) ";\n st.shared.u32 [t1+36], t0;\n"
#endif
        "sub.u32 t0, ra, %2;\n" JIG "shr.u32 %0, t0, 5;\n mad.lo.u32 t0, t0, 96, %1;\n xor.b32 t1, t0, 64;\n"
        STH(0, t0, t1) STH(1, t1, t0) STH(2, t0, t1) STH(3, t1, t0)
        "setp.eq.u32 p, %0, 12;\n @p bra.uni DONE;\n"
        STH(4, t0, t1) STH(5, t1, t0)
        "DONE:\n}\n" : "+r"(head) : "r"(xl), "r"(rl), "r"(cl) : "memory");
    return head;
}

#define RMMA(D, Q, B0, B1) "mma.sync.aligned.m16n8k16.row.col.f32.bf16.bf16.f32 {" #D "0," #D "1," #D "2," #D "3}, {w" #Q "_0,w" #Q "_1,w" #Q "_2,w" #Q "_3}, {" #B0 "," #B1 "}, {fz,fz,fz,fz};\n"
#define RPK(I, D) "cvt.rn.bf16x2.f32 u" #I ", " #D "2, " #D "0;\n cvt.rn.bf16x2.f32 v" #I ", " #D "3, " #D "1;\n"
#define RG(Q0, Q1, Q2, Q3, B0, B1, A, OFF) \
    RMMA(da, Q0, B0, B1) RMMA(db, Q1, B0, B1) RMMA(dc, Q2, B0, B1) RMMA(dd, Q3, B0, B1) \
    RPK(0, da) RPK(1, db) RPK(2, dc) RPK(3, dd) \
    "st.shared.v4.u32 [" #A "+" #OFF "], {u0,u1,u2,u3};\n st.shared.v4.u32 [" #A "+" #OFF "+4*" STR(RSTR) "], {v0,v1,v2,v3};\n"
#define RSPLIT(M) "setp.eq.u32 pk, ro, " #M ";\n @pk exit;\n"
#if RSPL & 2
#define RS1 RSPLIT(1)
#else
#define RS1
#endif
#if RSPL & 4
#define RS2 RSPLIT(2)
#else
#define RS2
#endif
#if RSPL & 8
#define RS3 RSPLIT(3)
#else
#define RS3
#endif
#ifdef NOLOAD
#define RTX "0"
#else
#define RTX "16384"
#endif
#ifdef DBG_R
#define RW0 "mov.u32 tw, %%clock;\n"
#define RW1 "mov.u32 t0, %%clock;\n sub.u32 t0, t0, tw;\n add.u32 %0, %0, t0;\n"
#else
#define RW0
#define RW1
#endif
#ifdef XREC
#define RG2(B0, B1)
#else
#define RG2(B0, B1) RG(8, 9, 10, 11, B0, B1, a0, 128) RS3 RG(12, 13, 14, 15, B0, B1, a0, 448)
#endif
#define RSTAGE(ID, B0, B1, SEL, PRE, MID) \
    "@!pw bra.uni RW" #ID ";\n RR" #ID ":\n" PRE \
    "mbarrier.test_wait.parity.shared::cta.b64 pw, [sb+" STR(SM_EMPTY) "+16-8*" STR(NR) "], 0;\n" \
    "add.u32 a0, ro, %2;\n add.u32 a2, ro, %4;\n" \
    RG(0, 1, 2, 3, B0, B1, a0, 0) RS1 RG(4, 5, 6, 7, B0, B1, a0, 320) RS2 MID \
    "selp.b32 t0, " SEL ", pe;\n" \
    "mma.sync.aligned.m16n8k8.row.col.f32.bf16.bf16.f32 {da0,da1,da2,da3}, {%5,%6}, {t0}, {fz,fz,fz,fz};\n" RPK(0, da) \
    "st.shared.u32 [a2], u0;\n st.shared.u32 [a2+4*" STR(RSTR) "], v0;\n" \
    RG2(B0, B1) \
    "bar.warp.sync 0xffffffff;\n elect.sync _|l0, 0xffffffff;\n" \
    "@l0 mbarrier.arrive.expect_tx.shared::cta.b64 _, [sb+" STR(SM_FULL) "], " RTX ";\n" \
    "add.u32 sb, sb, 16;\n add.u32 ro, ro, 16*" STR(RSTR) ";\n setp.ge.u32 pk, ro, " STR(SM_EID) ";\n @pk sub.u32 ro, ro, 8*" STR(NR) "*" STR(RSTR) ";\n" \
    "setp.ge.u32 pk, sb, %9;\n @pk bra.uni REND;\n"
#define RWAIT(ID) "RW" #ID ":\n" RW0 "mov.u32 t1, 0;\n" \
    "RV" #ID ":\n mbarrier.try_wait.parity.shared::cta.b64 pk, [sb+" STR(SM_EMPTY) "-8*" STR(NR) "], 0;\n" \
    "add.u32 t1, t1, 1;\n setp.lt.and.u32 pk, t1, 400000, !pk;\n @pk bra.uni RV" #ID ";\n" RW1 "bra.uni RR" #ID ";\n"
#define RLD1(S, I, J, E) "shl.b32 " #E ", " #E ", 2;\n lop3.b32 " #E ", " #E ", 0xFFFFC, tt, 0xEA;\n mad.wide.u32 ad, " #E ", 8, %10;\n " RLDG ".v2.u32 {" #S #I "," #S #J "}, [ad];\n"
#define RLD2(S, I, E, F) "selp.b32 t1, " #E ", " #F ", pe;\n and.b32 t1, t1, -2;\n mad.wide.u32 ad, t1, 2, %11;\n " RLDG ".u32 " #S #I ", [ad];\n"
#define RLOAD(S, DEP) "lop3.b32 tt, " #DEP ", %12, %7, 0xEA;\n" \
    RLD1(S, 0, 1, e0) RLD1(S, 2, 3, e1) RLD2(S, 8, e0, e1) RLD1(S, 4, 5, e2) RLD1(S, 6, 7, e3) RLD2(S, 9, e2, e3)
#define REID1(I) "ld.shared.u32 e" #I ", [ea+" STR(SM_EID) "+64*" #I "];\n"
#define REID REID1(0) REID1(1) REID1(2) REID1(3) "add.u32 ea, ea, 256;\n"
#define RPF "mad.wide.u32 ad, pf, 4096, %14;\n add.u32 pf, pf, 2*" STR(NCTA) ";\n setp.lt.u32 pk, pf, %3;\n selp.b32 pf, pf, %3, pk;\n" \
    "elect.sync _|l0, 0xffffffff;\n @l0 cp.async.bulk.prefetch.L2.global [ad], 4096;\n"
#define RLDW(Q) "ldmatrix.sync.aligned.m8n8.x4.trans.shared.b16 {w" #Q "_0,w" #Q "_1,w" #Q "_2,w" #Q "_3}, [%1+2*(64*(2*(" #Q ">>3)+((" #Q "&3)>>1))+8*((2*(" #Q "&1)+(" #Q "&4))^(2*(" #Q "&2))))];\n"
__device__ __forceinline__ unsigned recorder(const Params& p, int hw, int nst, unsigned cg0, unsigned cg1) {
    const int lane = threadIdx.x & 31, g = lane >> 2, t = lane & 3, mi = lane >> 3, r = lane & 7;
    const unsigned wa = SM_WR + (4 * (r >> 1) + (r & 1) + 2 * (mi >> 1)) * 528 + (mi & 1) * 16;
    unsigned ewait = 0;
    asm volatile("{\n"
        ".reg .b32 w0_<4>, w1_<4>, w2_<4>, w3_<4>, w4_<4>, w5_<4>, w6_<4>, w7_<4>, w8_<4>, w9_<4>, w10_<4>, w11_<4>, w12_<4>, w13_<4>, w14_<4>, w15_<4>;\n"
        ".reg .b32 x<10>, y<10>, e<4>, u<4>, v<4>, a<3>, t<2>, tt, tw, ea, sb, ro, pf;\n .reg .b64 ad;\n"
        ".reg .f32 da<4>, db<4>, dc<4>, dd<4>, fz;\n .reg .pred pw, pk, pe, l0;\n"
        RLDW(0) RLDW(1) RLDW(2) RLDW(3) RLDW(4) RLDW(5) RLDW(6) RLDW(7) RLDW(8) RLDW(9) RLDW(10) RLDW(11) RLDW(12) RLDW(13) RLDW(14) RLDW(15)
        "mov.f32 fz, 0f00000000;\n and.b32 t0, %7, 1;\n setp.eq.u32 pe, t0, 0;\n"
        "mov.u32 pf, %15;\n mad.lo.u32 ea, %13, 32, %8;\n shl.b32 sb, %13, 3;\n mad.lo.u32 ro, %13, 8*" STR(RSTR) ", " STR(SM_R) ";\n"
        "bar.sync 0, 512;\n"
        "setp.lt.u32 pw, sb, %9;\n @!pw bra.uni REND;\n"
        REID RLOAD(x, %12) REID
        "RTOP:\n"
        RSTAGE(0, x0, x1, "x8, 0", RLOAD(y, x0), ) RSTAGE(1, x2, x3, "0, x8", , ) RSTAGE(2, x4, x5, "x9, 0", , RPF) RSTAGE(3, x6, x7, "0, x9", , REID)
        RSTAGE(4, y0, y1, "y8, 0", RLOAD(x, y0), ) RSTAGE(5, y2, y3, "0, y8", , ) RSTAGE(6, y4, y5, "y9, 0", , RPF) RSTAGE(7, y6, y7, "0, y9", , REID)
        "bra.uni RTOP;\n"
        RWAIT(0) RWAIT(1) RWAIT(2) RWAIT(3) RWAIT(4) RWAIT(5) RWAIT(6) RWAIT(7)
        "REND:\n and.b32 t0, sb, 8;\n and.b32 %0, %0, -16;\n or.b32 %0, %0, t0;\n}\n"
        : "+r"(ewait)
        : "r"(wa), "r"(t * RSTR + g * 16), "r"(p.N / 2 - 1), "r"(t * RSTR + 256 + g * 4), "r"(cg0), "r"(cg1), "r"(t),
          "r"(((g >> 1) + 4 * (g & 1)) * 4), "r"(nst * 8), "l"(p.ea), "l"(p.sh), "r"(p.zero), "r"(hw), "l"(p.x),
          "r"(min((int)blockIdx.x + (PFLEAD / 2 + hw) * NCTA, p.N / 2 - 1)) : "memory");
    return ewait;
}
#ifdef NOLOAD
#define TROW(J, Z0, Z1)
#else
#define TROW(J, Z0, Z1) "@l0 cp.async.bulk.tensor.3d.shared::cluster.global.mbarrier::complete_tx::bytes [xs+" STR(SM_X) "+" #J "*2048], [mp, {" #Z0 ",k" #J "," #Z1 "}], [mb];\n"
#endif
#ifdef DBG_H
#define TL "add.u32 %0, %0, c;\n"
#else
#define TL
#endif
#ifndef TCLK
#define TCLK "mov.u64 ad, %%clock64;\n cvt.u32.u64 c, ad;\n"
#endif
#define TDL "mul.hi.u32 dl, q1, rt;\n add.u32 dl, dl, %4;\n shr.u32 q0, q0, 18;\n shr.u32 q1, q1, 18;\n shr.u32 q2, q2, 18;\n shr.u32 q3, q3, 18;\n"
__device__ __forceinline__ unsigned issuer(const CUtensorMap* tm, const Params& p, int nst, unsigned T0) {
    unsigned late = 0;
    asm volatile("{\n"
        ".reg .b32 k<4>, q<4>, z<8>, xs, sa, sb, mb, dl, c, n, rt;\n .reg .b64 ad, mp;\n .reg .pred pw, pk, l0;\n"
        "mov.u32 n, " STR(SM_NEXT) ";\n ld.shared.v4.u32 {z0,z1,z2,z3}, [n+-32];\n ld.shared.v4.u32 {z4,z5,z6,z7}, [n+-16];\n"
        "ld.shared.u64 ad, [n+-48];\n add.u64 mp, ad, %1;\n ld.shared.u32 rt, [n+-40];\n add.u32 rt, rt, %5;\n"
        "mov.u32 sa, 0;\n mov.u32 xs, %2;\n mov.u32 sb, 0;\n"
        "ld.shared.v4.u32 {q0,q1,q2,q3}, [sa+" STR(SM_EID) "];\n" TDL "bra.uni TW;\n"
        "TR:\n" TL
        "elect.sync _|l0, 0xffffffff;\n"
        "shl.b32 k0, q0, 2;\n shl.b32 k1, q1, 2;\n shl.b32 k2, q2, 2;\n shl.b32 k3, q3, 2;\n add.u32 mb, sb, " STR(SM_FULL) ";\n"
        "add.u32 sa, sa, 16;\n ld.shared.v4.u32 {q0,q1,q2,q3}, [sa+" STR(SM_EID) "];\n"
        "shr.u32 sb, sa, 2;\n and.b32 sb, sb, -8;\n"
        "mbarrier.test_wait.parity.shared::cta.b64 pw, [sb+" STR(SM_EMPTY) "-8*" STR(NX) "], 0;\n"
        TROW(0, z0, z1) TROW(1, z2, z3) TROW(2, z4, z5) TROW(3, z6, z7) TCLK TDL
        "sub.u32 c, c, dl;\n setp.lt.and.u32 pw, sb, %3, pw;\n setp.ge.and.s32 pw, c, 0, pw;\n"
        "add.u32 xs, xs, 8192;\n setp.eq.u32 pk, xs, " STR(SM_R) "-" STR(SM_X) ";\n selp.b32 xs, 0, xs, pk;\n"
        "@pw bra.uni TR;\n"
        "TW:\n setp.ge.u32 pk, sb, %3;\n @pk bra.uni TEND;\n mov.u32 n, 0;\n"
        "TV:\n mbarrier.try_wait.parity.shared::cta.b64 pk, [sb+" STR(SM_EMPTY) "-8*" STR(NX) "], 0;\n"
        "add.u32 n, n, 1;\n setp.lt.and.u32 pk, n, 400000, !pk;\n @pk bra.uni TV;\n"
        "TS:\n" TCLK "sub.u32 c, c, dl;\n setp.lt.s32 pk, c, 0;\n @pk bra.uni TS;\n bra.uni TR;\n"
        "TEND:\n}\n"
        : "+r"(late)
        : "l"(tm), "r"(((NX - nst % NX) % NX) * 16384), "r"(nst * 8), "r"(T0), "r"(p.rate)
#ifdef DBG_TR
          , "l"(g_trace + blockIdx.x * 720)
#endif
        : "memory");
    return late;
}

__device__ __forceinline__ void slow_path(const Params& p) {
    const int lane = threadIdx.x & 31, warp = threadIdx.x >> 5;
#pragma unroll 1
    for (int nl = warp; nl < NPC; nl += 16) {
        const int node = blockIdx.x * NPC + nl;
        float acc[4][8];
#pragma unroll
        for (int w = 0; w < 4; w++)
#pragma unroll
            for (int j = 0; j < 8; j++) acc[w][j] = 0.f;
        if (node < p.N) {
#pragma unroll 1
            for (int e0 = 0; e0 < p.E; e0 += 32) {
                int e = e0 + lane;
                unsigned m = __ballot_sync(~0u, e < p.E && p.dst[e] == node);
                while (m) {
                    int ee = e0 + __ffs(m) - 1; m &= m - 1;
                    int s = p.src[ee];
                    float rw[8];
#pragma unroll
                    for (int j = 0; j < 8; j++) rw[j] = 0.f;
#pragma unroll 1
                    for (int k = 0; k < 16; k++) {
                        float a = __bfloat162float(p.ea[(size_t)ee * 16 + k]);
#pragma unroll
                        for (int j = 0; j < 8; j++) rw[j] += a * __bfloat162float(p.wr[k * 256 + lane * 8 + j]);
                    }
#pragma unroll 1
                    for (int u = 0; u < 4; u++) {
                        float y[8];
#pragma unroll
                        for (int j = 0; j < 8; j++) y[j] = rw[j] * __bfloat162float(p.x[((size_t)s * 4 + u) * 256 + lane * 8 + j]);
#pragma unroll
                        for (int w = 0; w < 4; w++) {
                            float a = 0.f;
#pragma unroll
                            for (int v = 0; v < 4; v++) a += __bfloat162float(p.cg[u * 16 + v * 4 + w]) * __bfloat162float(p.sh[(size_t)ee * 4 + v]);
#pragma unroll
                            for (int j = 0; j < 8; j++) acc[w][j] += a * y[j];
                        }
                    }
                }
            }
        }
#pragma unroll
        for (int w = 0; w < 4; w++) {
            int R = nl * 4 + w;
            sts128(SM_H + (lane >> 3) * HPANEL + R * 128 + (((lane & 7) ^ (R & 7)) << 4),
                   pack2(acc[w][0], acc[w][1]), pack2(acc[w][2], acc[w][3]), pack2(acc[w][4], acc[w][5]), pack2(acc[w][6], acc[w][7]));
        }
    }
}

template <int NN>
__device__ __forceinline__ void out_chunk(float* d, unsigned stg, const CUtensorMap* tmo, int wg, int row0, bool first, unsigned a, bool lead) {
    if (!first) {
        if (lead) asm volatile("cp.async.bulk.wait_group.read 0;" ::: "memory");
    }
    asm volatile("bar.sync %0, 128;" ::"r"(wg + 1) : "memory");
#pragma unroll
    for (int n = 0; n < NN / 8; n += 2)
        stsm4t(a + n * 1024, pack2(d[4 * n], d[4 * n + 1]), pack2(d[4 * n + 2], d[4 * n + 3]), pack2(d[4 * n + 4], d[4 * n + 5]), pack2(d[4 * n + 6], d[4 * n + 7]));
    fence_async();
    asm volatile("bar.sync %0, 128;" ::"r"(wg + 1) : "memory");
    if (lead) {
#pragma unroll
        for (int j = 0; j < NN / 16; j++) tma_st(tmo, stg + j * 2048, wg * 64, row0 + j * 16);
        asm volatile("cp.async.bulk.commit_group;" ::: "memory");
    }
}

__global__ void __launch_bounds__(512, 1)
mace_kernel(const __grid_constant__ Params p, const __grid_constant__ CUtensorMap tmx, const __grid_constant__ CUtensorMap tmw,
            const __grid_constant__ CUtensorMap tmo) {
    extern __shared__ __align__(1024) char smem_raw[];
    const unsigned tstart = clk();
    const int tid = threadIdx.x, cta = blockIdx.x;
    const int e0 = cta * EPC + tid * 4;
    const bool has = tid < EPC / 4 && e0 < p.Ef;
    uint4 s4, d4;
    asm volatile("{.reg .pred q; setp.ne.u32 q, %10, 0;\n @q ld.global.nc.v4.u32 {%0,%1,%2,%3}, [%8];\n @q ld.global.nc.v4.u32 {%4,%5,%6,%7}, [%9];}"
        : "=r"(d4.x), "=r"(d4.y), "=r"(d4.z), "=r"(d4.w), "=r"(s4.x), "=r"(s4.y), "=r"(s4.z), "=r"(s4.w) : "l"(p.dst + e0), "l"(p.src + e0), "r"((int)has) : "memory");
    const int lane = tid & 31, warp = __shfl_sync(~0u, tid >> 5, 0);
    const unsigned wbar = SM_MISC, totA = SM_MISC + 80;
    bool slow = p.Ef == 0;
    int total = 0, nst = 0;
    unsigned T0 = 0, cg0 = 0, cg1 = 0, dsc[4];
    if (slow) {
        if (tid < 8) bar_init(wbar + tid * 8, 1);
    } else if (warp >= NXT / 32) {
        unsigned* const ctr = (unsigned*)(p.xch + NCTA * NCTA * NCH);
        unsigned epn;
        if (warp == 15) {
            asm volatile("ld.relaxed.gpu.global.u32 %0, [%1];" : "=r"(epn) : "l"(ctr));
        } else {
#pragma unroll
            for (int k = 0; k < 6; k++) {
                const unsigned i = lane + k * 32, c = i < CAPP / 16 + 8 || i >= CAPP / 8 + 8 ? 0xFFFFFu : 0xFFFF8u;
                sts128(i < CAPP / 8 + 8 ? SM_FULL + i * 16 : wbar + (i - CAPP / 8 - 8) * 16, c << 1, c << 11, c << 1, c << 11);
            }
            fence_async();
            __syncwarp();
            if (lane < 16) asm volatile("mbarrier.arrive.shared::cta.b64 _, [%0];" ::"r"(SM_EMPTY + (lane - 16) * 8) : "memory");
        }
        uint4 w4[8];
        unsigned c4[4];
#pragma unroll
        for (int k = 0; k < 8; k++) asm volatile("ld.global.nc.v4.u32 {%0,%1,%2,%3}, [%4];" : "=r"(w4[k].x), "=r"(w4[k].y), "=r"(w4[k].z), "=r"(w4[k].w) : "l"((const uint4*)p.wr + (tid - NXT + k * 64)));
#pragma unroll
        for (int k = 0; k < 4; k++) asm volatile("ld.global.nc.u16 %0, [%1];" : "=r"(c4[k]) : "l"(p.cg + (lane & 4) * 8 + (lane & 2) * 4 + (lane >> 3) + (k & 1) * 4 + (k & 2) * 8));
        auto put = [&]() {
#pragma unroll
            for (int k = 0; k < 8; k++) sts128(SM_WR + (warp - NXT / 32 + 2 * k) * 528 + lane * 16, w4[k].x, w4[k].y, w4[k].z, w4[k].w);
            asm volatile("prmt.b32 %0, %2, %3, 0x5410;\n prmt.b32 %1, %4, %5, 0x5410;" : "=&r"(cg0), "=r"(cg1) : "r"(c4[0]), "r"(c4[1]), "r"(c4[2]), "r"(c4[3]));
        };
        if (warp == 15) {
            epn = (epn | 255) + 1;
            sts64(totA, epn, 0);
            narrive<7, NXT + 32>();
            nsync<10, NXT + 32>();
            if (lane == 0) asm volatile("red.relaxed.gpu.global.add.u32 [%0], %1;" ::"l"(ctr), "r"(cta ? 1 : 257 - NCTA) : "memory");
            put();
            while (clk() - tstart < POLLT);
            unsigned v; int it = 0;
            do asm volatile("ld.relaxed.gpu.global.u32 %0, [%1];" : "=r"(v) : "l"(ctr) : "memory");
            while (v != epn && ++it < 4096);
            narrive<8, NXT + 32>();
#ifdef DBG_PRO
            sts32(totA + 16, it * 2);
#endif
            nsync<9, NXT + 32>();
            uint4 u[NBW];
#pragma unroll
            for (int q = 0; q < NBW; q++) u[q] = lds128(SM_BKT + (lane * NBW + q) * 16);
            const unsigned mx = lds32(SM_CNT + min(lane, NXT / 32 - 1) * 4), bad = lds32(totA + 4);
            unsigned sum = 0;
#pragma unroll
            for (int q = 0; q < NBW; q++) sum += u[q].x + u[q].y + u[q].z + u[q].w;
            unsigned inc = sum;
#pragma unroll
            for (int o = 1; o < 32; o <<= 1) asm volatile("{.reg .pred q; .reg .b32 t; shfl.sync.up.b32 t|q, %0, %1, 0, -1;\n @q add.u32 %0, %0, t;}" : "+r"(inc) : "r"(o));
            sum = inc - sum;
#pragma unroll
            for (int q = 0; q < NBW; q++) {
                const unsigned a2 = sum + u[q].x + u[q].y;
                sts128(SM_BKT + (lane * NBW + q) * 16, sum, sum + u[q].x, a2, a2 + u[q].z);
                sum = a2 + u[q].z + u[q].w;
            }
            const unsigned t0 = tstart + ((__reduce_max_sync(~0u, mx) & 0xFFF8) << 1) + T0DELTA;
            if (lane == 31) sts64(totA + 8, (inc >> 2) + bad, t0);
        } else {
            if (elect()) {
                asm volatile("prefetch.tensormap [%0];" ::"l"(&tmx) : "memory");
                asm volatile("prefetch.tensormap [%0];" ::"l"(&tmw) : "memory");
                asm volatile("prefetch.tensormap [%0];" ::"l"(&tmo) : "memory");
                const int r = cta * PFLEAD, m = min(PFLEAD, p.N - r);
#ifdef PFT
                while (clk() - tstart < PFT);
#endif
                if (m > 0) pf_l2(p.x + (size_t)r * 1024, m * 2048);
                if (cta < 128) pf_l2(p.wo + cta * 512, 1024);
#pragma unroll 1
                for (int i = 0; i < (PFD ? EPC / 64 : 0); i++) {
                    const int eb = (i * NCTA + cta) * 64, n = min(64, p.E - eb);
                    while (clk() - tstart < PF0 + i * PFD);
                    if (n > 0) { pf_l2(p.ea + (size_t)eb * 16, n * 32); pf_l2(p.sh + (size_t)eb * 4, n * 8); }
                }
            }
            put();
        }
        cta_sync();
        total = __shfl_sync(~0u, lds32(totA + 8), 0);
        slow = total > CAP;
        nst = (total + 7) >> 3;
    } else {
        {
            const unsigned du = DUM + (((cta * NCH + tid) & 31) << (18 + BSH));
#pragma unroll
            for (int k = 0; k < 3; k++) sts128(SM_STAGE + (tid + k * NXT) * 16, du, du, du, ~0u);
            if (tid < NCTA) sts32(SM_CNT + tid * 4, 0);
        }
        TK(24, e0);
        nsync<6, NXT>();
        TK(0, e0);
        const bool h2 = tid < NCTA * NCH - 2 * NXT;
        unsigned cc[3];
        const char* xo[3];
#pragma unroll
        for (int k = 0; k < 3; k++) {
            const unsigned i = tid + k * NXT;
            cc[k] = (i * 6554) >> 16;
            xo[k] = pin64((const char*)(p.xch + (cc[k] * ((NCTA - 1) * NCH) + cta * NCH + i)));
        }
        TK(26, d4.x);
        if (has) {
            const unsigned ss[4] = {s4.x, s4.y, s4.z, s4.w}, dd[4] = {d4.x, d4.y, d4.z, d4.w};
            unsigned c[4], o[4];
#pragma unroll
            for (int j = 0; j < 4; j++) { c[j] = __umulhi(dd[j], 0xFFFFFFFFu / NPC + 1); o[j] = atoms_add(SM_CNT + c[j] * 4, 0x15558); }
#pragma unroll
            for (int j = 0; j < 4; j++) {
                const unsigned dl = dd[j] - c[j] * NPC;
                sts32(SM_STAGE + (c[j] * (NCH * 4) + min(o[j] >> 16, NCH * 4 - 1)) * 4, (ss[j] << 18) + (tid * 4 + j) + dl * 2048 + (dl * 43 >> 8) * 4096);
            }
        }
        TK(28, e0);
        nsync<7, NXT + 32>();
        TK(1, e0);
        const unsigned ep = (lds32(totA) << 8) | 0x80000000u;
        {
            const unsigned tag = ep | (min((clk() - tstart) >> 4, 0x1FFFu) << 3);
            uint4 v[3];
#pragma unroll
            for (int k = 0; k < 3; k++) v[k] = lds128(SM_STAGE + (tid + k * NXT) * 16);
#pragma unroll
            for (int k = 0; k < 3; k++)
                if (k < 2 || h2) asm volatile(XST " [%0], {%1,%2,%3,%4};" ::"l"(xo[k]), "r"(v[k].x), "r"(v[k].y), "r"(v[k].z), "r"(tag + (v[k].w != ~0u)) : "memory");
        }
        narrive<10, NXT + 32>();
        TK(16, e0);
        if ((unsigned)__cvta_generic_to_shared(smem_raw) != SB) __trap();
        if (tid < NBW * 32 + 8) { const unsigned v = tid < NBW * 32 ? 0 : CAP * 4; sts128(SM_BKT + tid * 16, v, v, v, v); }
        if (tid < 384) { const unsigned v = tid < 381 ? (p.N - 1) << 18 : 0; sts128(SM_EID + tid * 16, v, v, v, v); }
        if (tid < 1392 / 4) sts128(SM_SRC + tid * 16, NCONS << 14, NCONS << 14, NCONS << 14, NCONS << 14);
        if (tid < 159) sts128(SM_BITS + tid * 16, 0, 0, 0, 0);
#pragma unroll
        for (int k = 0; k < 4; k++) {
            const unsigned pos = tid + k * (NCONS * 32), st = pos >> 3, j = pos & 7;
            dsc[k] = pin(pos | (((st % NX) * 8 + j) << 11) | ((((st % NR) * 8 + j) * (RSTR / 32)) << 21));
        }
        const char* const xi = pin64((const char*)(p.xch + cta * (NCTA * NCH) + tid));
        uint4 rc[3];
        rc[0].w = rc[1].w = 0;
        rc[2].w = h2 ? 0 : ep;
        rc[2].x = ~0u;
        nsync<8, NXT + 32>();
        TK(18, e0);
        {
            bool bad;
            int it = 0;
            do {
#pragma unroll
                for (int k = 0; k < 3; k++)
                    asm volatile("{.reg .pred q; .reg .b32 t; xor.b32 t, %3, %5; setp.gt.u32 q, t, 0xFFFF;\n @q ld.relaxed.gpu.global.v4.u32 {%0,%1,%2,%3}, [%4];}"
                                 : "+r"(rc[k].x), "+r"(rc[k].y), "+r"(rc[k].z), "+r"(rc[k].w) : "l"(xi + k * (NXT * 16)), "r"(ep) : "memory");
                bad = ((rc[0].w ^ ep) | (rc[1].w ^ ep) | (rc[2].w ^ ep)) > 0xFFFF;
            } while (__any_sync(~0u, bad) && ++it < 4096);
            if (bad || ((rc[0].w | rc[1].w | rc[2].w) & 1)) {
                rc[0].x = rc[1].x = rc[2].x = ~0u;
                sts32(totA + 4, CAP + 1);
            }
#ifdef DBG_PRO
            if (tid == 0) sts32(totA + 20, it * 2);
#endif
        }
        TK(2, e0);
        unsigned ord[3][3], ba[3][3], ve[3][3];
#pragma unroll
        for (int k = 0; k < 3; k++) {
            const unsigned rr[3] = {rc[k].x, rc[k].y, rc[k].z};
            if (rr[0] < DUM) {
#pragma unroll
                for (int j = 0; j < 3; j++) { ba[k][j] = pin((rr[j] >> (18 + BSH)) * 4); ord[k][j] = atoms_add(SM_BKT + ba[k][j], 4); }
            }
        }
        sts32(SM_CNT + warp * 4, __reduce_max_sync(~0u, max(rc[0].w, max(rc[1].w, rc[2].w))));
        narrive<9, NXT + 32>();
        TK(15, e0);
#pragma unroll
        for (int k = 0; k < 3; k++) {
            const unsigned rr[3] = {rc[k].x, rc[k].y, rc[k].z};
#pragma unroll
            for (int j = 0; j < 3; j++) ve[k][j] = pin((rr[j] & 0xFFFC07FF) + cc[k] * EPC);
        }
        cta_sync();
        TK(19, e0);
        total = __shfl_sync(~0u, lds32(totA + 8), 0);
        T0 = lds32(totA + 12);
#pragma unroll
        for (int k = 0; k < 3; k++) {
            if (rc[k].x < DUM) {
#pragma unroll
                for (int j = 0; j < 3; j++) ord[k][j] += lds32(SM_BKT + ba[k][j]);
#pragma unroll
                for (int j = 0; j < 3; j++)
                    asm volatile("{.reg .pred q; setp.lt.u32 q, %0, " STR(CAP) "*4;\n @q st.shared.u32 [%0+" STR(SM_EID) "], %1;}" ::"r"(ord[k][j]), "r"(ve[k][j]) : "memory");
            }
        }
        slow = total > CAP;
        if (!slow) {
            if (warp < NCONS) narrive<0, 512>();
#pragma unroll
            for (int k = 0; k < 3; k++) {
                const unsigned rr[3] = {rc[k].x, rc[k].y, rc[k].z};
                if (rr[0] < DUM) {
#pragma unroll
                    for (int j = 0; j < 3; j++)
                        asm volatile("{.reg .pred q; setp.lt.u32 q, %0, " STR(CAP) "*4;\n @q st.shared.u32 [%0+" STR(SM_SRC) "], %1;}" ::"r"(ord[k][j]), "r"(rr[j]) : "memory");
                }
            }
            if (warp == NCONS) narrive<11, NXT>();
        }
        nst = (total + 7) >> 3;
        const unsigned lim = (nst % NX) << 14;
#pragma unroll
        for (int k = 0; k < 4; k++) dsc[k] = pin(dsc[k] - lim + ((dsc[k] & 0x3C000) >= lim ? 0 : NX << 14));
        TK(20, e0);
#ifdef DBG_PRO
        if (tid == 0) { sts128(SM_NEXT + CAPP * 4, tk0, tk1, tk24, tk26); sts128(SM_NEXT + CAPP * 4 + 16, tk28, tk16, tk2, tk15); sts128(SM_NEXT + CAPP * 4 + 32, tk19, tk20, tk18, tstart); }
#endif
    }

    int wid = warp;
    if (slow) {
        asm volatile("fence.mbarrier_init.release.cluster;" ::: "memory");
        fence_async();
        cta_sync();
        if (tid < 4) { bar_expect(wbar + tid * 8, 16384); tma_2d(SB + tid * 16384, &tmw, wbar + tid * 8, tid * 64, 0); }
        slow_path(p);
    } else if (warp < NCONS) {
        nsync<11, NXT>();
        TK(3, tid);
        unsigned q[4], a[4];
        const bool k3 = warp * 32 + 3 * NCONS * 32 < total;
#pragma unroll
        for (int k = 0; k < 4; k++) if (k < 3 || k3) q[k] = lds32(SM_SRC + tid * 4 + k * (NCONS * 128));
#pragma unroll
        for (int k = 0; k < 4; k++) if (k < 3 || k3) {
            a[k] = ((q[k] >> 14) & 15) * (BW * 4) + warp * 4;
            asm volatile("red.shared.or.b32 [%0], %1;" ::"r"(SM_BITS + k * (NCONS * 4) + a[k]), "r"(1u << lane) : "memory");
        }
        __syncwarp();
#pragma unroll
        for (int k = 0; k < 4; k++) if (k < 3 || k3) a[k] = lds32(SM_BITS + k * (NCONS * 4) + a[k]);
#pragma unroll
        for (int k = 0; k < 4; k++) if (k < 3 || k3)
            sts32(SM_NEXT + k * (NCONS * 128) + ((warp * 32) | ((lane + 31 - __clz(__funnelshift_r(a[k], a[k], lane))) & 31)) * 4, dsc[k] | ((q[k] << 7) & 0x1C0000));
        asm volatile("bar.sync 5, %0;" ::"n"(NCONS * 32) : "memory");
        TK(21, tid);
        unsigned head;
        {
            const unsigned c = 31 - lane, m0 = lds32(SM_BITS + warp * (BW * 4) + c * 4), m1 = lds32(SM_BITS + warp * (BW * 4) + 128 + min(c, 12) * 4);
            const unsigned l0 = m0 ? c * 32 + 31 - __clz(m0) : CAPP - 1, l1 = m1 ? c * 32 + 1055 - __clz(m1) : CAPP - 1;
            const unsigned f0 = lds32(SM_NEXT + l0 * 4), f1 = lane ? lds32(SM_NEXT + l1 * 4) : 0x1C0000 | (warp << 21);
            const unsigned b0 = __ballot_sync(~0u, m0), b1 = __ballot_sync(~0u, m1) | 1, lt = (1u << lane) - 1;
            const unsigned h1 = __shfl_sync(~0u, f1, 31 - __clz(b1)), n1 = __shfl_sync(~0u, f1, 31 - __clz(b1 & lt));
            const unsigned h0 = __shfl_sync(~0u, f0, 31 - __clz(b0)), n0 = __shfl_sync(~0u, f0, 31 - __clz(b0 & lt));
            sts32(SM_NEXT + l0 * 4, b0 & lt ? n0 : h1);
            sts32(SM_NEXT + l1 * 4, n1);
            head = b0 ? h0 : h1;
            __syncwarp();
        }
        TK(22, tid);
#ifdef DBG_PRO
        if (tid == 0) sts128(SM_NEXT + CAPP * 4 + 48, tk3, tk21, tk22, 0);
#endif
        wid = consumer(head);
    } else if (warp == NCONS) {
        cta_sync();
        STAMPS(636 + 26, clk() | 1);
        const unsigned late = issuer(&tmx, p, nst, T0);
        wid = NCONS;
        STAMPS(11, clk() | 1); STAMPS(14, lds32(SM_MISC + 104)); STAMPS(12, tstart & ~1);
#pragma unroll 1
        for (int i = 0; i < 4; i++) {
            bwait(SM_EMPTY + (nst + i - NX) * 8);
            if (elect()) { bar_expect(wbar + i * 8, 16384); tma_2d(SB + i * 16384, &tmw, wbar + i * 8, i * 64, 0); }
        }
#ifdef DBG_TR
        for (int i = lane; i < nst; i += 32) g_trace[(cta * 180 + i) * 4 + 3] = lds32(SM_TR + i * 8) - T0;
#endif
#ifdef DBG_PRO
        if (lane < 15) { const unsigned ix[15] = {0, 1, 24, 26, 28, 16, 2, 15, 19, 20, 18, 31, 3, 21, 22}; unsigned j = 0;
#pragma unroll
            for (int q = 0; q < 15; q++) j = lane == q ? ix[q] : j;
            const unsigned v = lds32(SM_NEXT + CAPP * 4 + lane * 4); g_times[cta * 32 + j] = j == 31 ? v & ~1 : v | 1; }
        STAMPW(13, lds32(totA + 16)); STAMPW(17, lds32(totA + 20));
#endif
#ifdef DBG_H
        STAMPS(8, late & ~1);
#endif
        STAMPS(10, clk() | 1); STAMPS(7, T0 | 1);
    } else {
        const unsigned ewait = recorder(p, __shfl_sync(~0u, (tid >> 5) & 1, 0), nst, cg0, cg1);
        wid = NCONS + 1 + ((ewait >> 3) & 1);
#ifdef DBG_R
        if (wid == 15) STAMPW(12, ewait); else STAMPW(11, ewait);
#endif
    }

    wid = __shfl_sync(~0u, wid, 0);
    const int wg = wid >> 2, wq = wid & 3;
    int ln;
    asm volatile("mov.u32 %0, %%laneid;" : "=r"(ln));
    const bool lead = wq == 0 && ln == 0;
    unsigned af[16][4];
    const unsigned wt = SB + wg * 16384;
    const unsigned wa = wt + (((ln >> 4) * 8 + (ln & 7)) << 7) + (((2 * wq + ((ln >> 3) & 1)) ^ (ln & 7)) << 4);
    STAMPL(13);
    bwait(wbar + wg * 8);
#pragma unroll
    for (int k = 0; k < 8; k++) ldsm4t(af[k], wa + k * 2048);
    fence_async();
    cta_sync();
    STAMPL(5);
    if (lead) { bar_expect(wbar + 32 + wg * 8, 16384); tma_2d(wt, &tmw, wbar + 32 + wg * 8, wg * 64, 128); }
    const uint64_t desc0 = (uint64_t)(((SM_H) >> 4) & 0x3FFF) | (1ull << 16) | (64ull << 32) | (1ull << 62);
    float d[32];
    const int row0 = cta * (NPC * 4);
    wg_fence();
#pragma unroll
    for (int k = 0; k < 8; k++) wgmma_rs<64>(d, af[k], desc0 + (k >> 2) * (HPANEL >> 4) + (k & 3) * 2, k != 0);
    wg_commit();
    bwait(wbar + 32 + wg * 8);
#pragma unroll
    for (int k = 0; k < 8; k++) ldsm4t(af[8 + k], wa + k * 2048);
    wg_fence();
#pragma unroll
    for (int k = 8; k < 16; k++) wgmma_rs<64>(d, af[k], desc0 + (k >> 2) * (HPANEL >> 4) + (k & 3) * 2, 1);
    wg_commit();
    wg_wait0();
    out_chunk<64>(d, wt, &tmo, wg, row0, true, wa, lead);
#pragma unroll 1
    for (int c = 1; c < 4; c++) {
        wg_fence();
#pragma unroll
        for (int k = 0; k < 16; k++) wgmma_rs<64>(d, af[k], desc0 + c * 512 + (k >> 2) * (HPANEL >> 4) + (k & 3) * 2, k != 0);
        wg_commit();
        wg_wait0();
        out_chunk<64>(d, wt, &tmo, wg, row0 + c * 64, false, wa, lead);
    }
    wg_fence();
#pragma unroll
    for (int k = 0; k < 16; k++) wgmma_rs<48>(d, af[k], desc0 + 4 * 512 + (k >> 2) * (HPANEL >> 4) + (k & 3) * 2, k != 0);
    wg_commit();
    wg_wait0();
    out_chunk<48>(d, wt, &tmo, wg, row0 + 256, false, wa, lead);
    if (lead) asm volatile("cp.async.bulk.wait_group.read 0;" ::: "memory");
    STAMPL(6);
#ifdef DBG_TIMES
    if (wid == 8) STAMPS(4, clk() | 1);
    cta_sync();
    if (wid == 0 && ln >= 4 && ln < 21) g_times[cta * 32 + (ln == 12 ? 31 : ln)] = lds32(SM_BITS + ln * 4);
#endif
#ifdef DBG_GT
    { unsigned g; asm volatile("mov.u32 %0, %%globaltimer_lo;" : "=r"(g)); STAMPW(30, g & ~1); }
#endif
}

typedef CUresult (*EncFn)(CUtensorMap*, CUtensorMapDataType, cuuint32_t, void*, const cuuint64_t*, const cuuint64_t*, const cuuint32_t*,
                          const cuuint32_t*, CUtensorMapInterleave, CUtensorMapSwizzle, CUtensorMapL2promotion, CUtensorMapFloatOOBfill);

extern "C" void kernel_launch(void* const* d_in, const int* in_sizes, int n_in, void* d_out, int out_size) {
    static EncFn enc = nullptr;
    static int nsm = 0;
    static void* xch = nullptr;
    if (!enc) {
        void* fn = nullptr; cudaDriverEntryPointQueryResult qr;
        cudaGetDriverEntryPoint("cuTensorMapEncodeTiled", &fn, cudaEnableDefault, &qr);
        enc = (EncFn)fn;
        cudaGetSymbolAddress(&xch, g_xch);
        int dev = 0; cudaGetDevice(&dev);
        cudaDeviceGetAttribute(&nsm, cudaDevAttrMultiProcessorCount, dev);
        cudaFuncSetAttribute(mace_kernel, cudaFuncAttributeMaxDynamicSharedMemorySize, SM_TOTAL);
    }
    Params p;
    p.x = (const __nv_bfloat16*)d_in[0]; p.src = (const int*)d_in[1]; p.dst = (const int*)d_in[2];
    p.sh = (const __nv_bfloat16*)d_in[3]; p.ea = (const __nv_bfloat16*)d_in[4]; p.cg = (const __nv_bfloat16*)d_in[5];
    p.wr = (const __nv_bfloat16*)d_in[6]; p.wo = (const __nv_bfloat16*)d_in[7];
    p.N = in_sizes[0] / 1024; p.E = in_sizes[1];
    p.Ef = (nsm >= NCTA && p.N <= NCTA * NPC && p.E <= NCTA * EPC && p.N > 1 && (p.E & 3) == 0) ? p.E : 0;
    p.xch = (uint4*)xch;
    p.rate = (unsigned)((double)PACE * ((double)p.E / 160000.0) * 16384.0 / (double)p.N);
    p.zero = 0;
    CUtensorMap tmx, tmw, tmo;
    const cuuint32_t es[3] = {1, 1, 1};
    {
        cuuint64_t dims[3] = {64, (cuuint64_t)p.N * 4, 4}; cuuint64_t str[2] = {512, 128}; cuuint32_t box[3] = {64, 4, 4};
        enc(&tmx, CU_TENSOR_MAP_DATA_TYPE_BFLOAT16, 3, d_in[0], dims, str, box, es, CU_TENSOR_MAP_INTERLEAVE_NONE, CU_TENSOR_MAP_SWIZZLE_128B, CU_TENSOR_MAP_L2_PROMOTION_NONE, CU_TENSOR_MAP_FLOAT_OOB_FILL_NONE);
    }
    {
        cuuint64_t dims[2] = {256, 256}; cuuint64_t str[1] = {512}; cuuint32_t box[2] = {64, 128};
        enc(&tmw, CU_TENSOR_MAP_DATA_TYPE_BFLOAT16, 2, d_in[7], dims, str, box, es, CU_TENSOR_MAP_INTERLEAVE_NONE, CU_TENSOR_MAP_SWIZZLE_128B, CU_TENSOR_MAP_L2_PROMOTION_NONE, CU_TENSOR_MAP_FLOAT_OOB_FILL_NONE);
    }
    {
        cuuint64_t dims[2] = {256, (cuuint64_t)p.N * 4}; cuuint64_t str[1] = {512}; cuuint32_t box[2] = {64, 16};
        enc(&tmo, CU_TENSOR_MAP_DATA_TYPE_BFLOAT16, 2, d_out, dims, str, box, es, CU_TENSOR_MAP_INTERLEAVE_NONE, CU_TENSOR_MAP_SWIZZLE_128B, CU_TENSOR_MAP_L2_PROMOTION_NONE, CU_TENSOR_MAP_FLOAT_OOB_FILL_NONE);
    }
    const int grid = p.Ef ? NCTA : (p.N + NPC - 1) / NPC;
    mace_kernel<<<grid, 512, SM_TOTAL>>>(p, tmx, tmw, tmo);
}
```

```cpp
#include <cuda_runtime.h>
#include <cuda_bf16.h>
#include <cuda.h>
#include <stdint.h>

#ifndef NX
#define NX 10
#endif
#ifndef NR
#define NR 9
#endif
#ifndef PACE
#define PACE 50000
#endif
#ifndef T0DELTA
#define T0DELTA 4900
#endif
#ifndef BSH
#define BSH 5
#endif
#ifndef POLLT
#define POLLT 3700
#endif
#ifndef PFT
#define PFT 5500
#endif
#ifndef PF1
#define PF1 0
#endif
#ifndef PFLEAD
#define PFLEAD 8
#endif
#ifndef RSPL
#define RSPL 10
#endif
#ifndef RLDG
#define RLDG "ld.global.nc"
#endif
#ifndef DISP
#define DISP 1
#endif
#ifndef XST
#define XST "st.relaxed.gpu.global.v4.u32"
#endif
#define NCTA 132
#define NPC 76
#define EPC 1216
#define NCH 10
#define CAP 1376
#define CAPP 1440
#define NCONS 13
#define RSTR 608
#define NBW ((((NCTA * NPC) >> BSH) + 128) / 128)

#define SB 1024
#define SM_X SB
#define SM_R (SM_X + NX * 16384)
#define SM_EID (SM_R + NR * 8 * RSTR)
#define SM_NEXT (SM_EID + 6144)
#define SM_H (SB + 65536)
#define HPANEL 38912
#define SM_FULL (SM_H + 4 * HPANEL)
#define SM_EMPTY (SM_FULL + CAPP + 128)
#define SM_SRC (SM_EMPTY + CAPP)
#define SM_BITS (SM_SRC + 1392 * 4)
#define SM_MISC (SM_BITS + 2544)
#define SM_TOTAL (SM_MISC + 128 - SB)
#define NXT 448
#define SM_STAGE SM_R
#define SM_CNT (SM_R + NXT * 48)
#define SM_WR (SM_CNT + 640)
#define SM_BKT (SM_WR + 16 * 528)
static_assert(SM_BKT + NBW * 512 + 128 <= SM_EID, "smem");
#define DUM ((unsigned)(NBW * 128) << (18 + BSH))
#define BW 45
static_assert(SM_NEXT + CAPP * 4 <= SM_FULL && SM_TOTAL <= 232448, "smem");
#define STR_(x) #x
#define STR(x) STR_(x)

__device__ uint4 g_xch[NCTA * NCTA * NCH + 8];
#ifdef DBG_TIMES
extern "C" { __device__ unsigned g_times[NCTA * 32]; }
#define STAMPV(m, i, v) asm volatile("{.reg .pred q; .reg .b32 t; .reg .b64 a, b; mov.u32 t, %%tid.x; and.b32 t, t, %0; setp.eq.u32 q, t, 0; mov.u32 t, %%ctaid.x; mov.u64 b, g_times; mad.wide.u32 a, t, 128, b; @q st.global.u32 [a+%1], %2;}" ::"n"(m), "n"((i) * 4), "r"(v) : "memory")
#define STAMP(i) STAMPV(1023, i, clk() | 0x1)
#define STAMPS(i, v) sts32(SM_BITS + (i) * 4, v)
#define STAMPL(i) if (wid == 0) STAMPS(i, clk() | 0x1)
#define STAMPW(i, v) asm volatile("{.reg .b32 t; .reg .b64 a, b; mov.u32 t, %%ctaid.x; mov.u64 b, g_times; mad.wide.u32 a, t, 128, b; st.global.u32 [a+%0], %1;}" ::"n"((i) * 4), "r"(v) : "memory")
#define TK(i, dep) unsigned tk##i; asm volatile("{.reg .b32 t; and.b32 t, %1, %2; mov.u32 %0, %%clock; add.u32 %0, %0, t;}" : "=r"(tk##i) : "r"(dep), "r"(p.zero) : "memory")
#define TKO(i) STAMPV(1023, i, tk##i | 1)
#ifndef DBG_PRO
#undef TK
#define TK(i, dep)
#endif
#else
#define STAMP(i)
#define STAMPL(i)
#define STAMPS(i, v)
#define STAMPV(m, i, v)
#define STAMPW(i, v)
#define TK(i, dep)
#define TKO(i)
#endif

struct Params {
    const int* src; const int* dst; uint4* xch; const __nv_bfloat16* wr;
    int Ef, N;
    const __nv_bfloat16* cg; const __nv_bfloat16* x; const __nv_bfloat16* sh; const __nv_bfloat16* ea; const __nv_bfloat16* wo;
    int E; unsigned rate, zero;
};

__device__ __forceinline__ unsigned clk() { unsigned c; asm volatile("mov.u32 %0, %%clock;" : "=r"(c)); return c; }
__device__ __forceinline__ bool elect() { unsigned p; asm volatile("{.reg .pred P; elect.sync _|P, 0xffffffff; selp.u32 %0,1,0,P;}" : "=r"(p)); return p; }
__device__ __forceinline__ bool try_wait(unsigned a) { unsigned ok; asm volatile("{.reg .pred p; mbarrier.try_wait.parity.shared::cta.b64 p,[%1],0; selp.u32 %0,1,0,p;}" : "=r"(ok) : "r"(a) : "memory"); return ok; }
__device__ __forceinline__ void bwait(unsigned a) { if (!try_wait(a)) { for (int i = 0; i < (1 << 18) && !try_wait(a); i++); } }
__device__ __forceinline__ unsigned pin(unsigned x) { unsigned y; asm volatile("mov.u32 %0, %1;" : "=r"(y) : "r"(x)); return y; }
__device__ __forceinline__ const char* pin64(const char* x) { const char* y; asm volatile("mov.u64 %0, %1;" : "=l"(y) : "l"(x)); return y; }
__device__ __forceinline__ void split(unsigned x, unsigned c) { asm volatile("{.reg .pred p; setp.eq.u32 p, %0, %1; @p exit;}" ::"r"(x), "r"(c) : "memory"); }
__device__ __forceinline__ void bar_init(unsigned a, unsigned c) { asm volatile("mbarrier.init.shared::cta.b64 [%0], %1;" ::"r"(a), "r"(c) : "memory"); }
__device__ __forceinline__ void bar_expect(unsigned a, unsigned bytes) { asm volatile("mbarrier.arrive.expect_tx.shared::cta.b64 _, [%0], %1;" ::"r"(a), "r"(bytes) : "memory"); }
__device__ __forceinline__ void bar_complete(unsigned a, unsigned bytes) { asm volatile("mbarrier.complete_tx.relaxed.cta.shared::cta.b64 [%0], %1;" ::"r"(a), "r"(bytes) : "memory"); }
__device__ __forceinline__ void fence_async() { asm volatile("fence.proxy.async.shared::cta;" ::: "memory"); }
template <int ID, int N> __device__ __forceinline__ void nsync() { asm volatile("bar.sync %0, %1;" ::"n"(ID), "n"(N) : "memory"); }
template <int ID, int N> __device__ __forceinline__ void narrive() { asm volatile("bar.arrive %0, %1;" ::"n"(ID), "n"(N) : "memory"); }
__device__ __forceinline__ void cta_sync() { asm volatile("bar.sync 0, 512;" ::: "memory"); }
__device__ __forceinline__ unsigned lds32(unsigned a) { unsigned v; asm volatile("ld.shared.u32 %0,[%1];" : "=r"(v) : "r"(a) : "memory"); return v; }
__device__ __forceinline__ unsigned lds16(unsigned a) { unsigned v; asm volatile("ld.shared.u16 %0,[%1];" : "=r"(v) : "r"(a) : "memory"); return v; }
__device__ __forceinline__ uint4 lds128(unsigned a) { uint4 v; asm volatile("ld.shared.v4.u32 {%0,%1,%2,%3},[%4];" : "=r"(v.x), "=r"(v.y), "=r"(v.z), "=r"(v.w) : "r"(a) : "memory"); return v; }
__device__ __forceinline__ void sts32(unsigned a, unsigned v) { asm volatile("st.shared.u32 [%0],%1;" ::"r"(a), "r"(v) : "memory"); }
__device__ __forceinline__ void sts16(unsigned a, unsigned v) { asm volatile("st.shared.u16 [%0],%1;" ::"r"(a), "r"(v) : "memory"); }
__device__ __forceinline__ void sts64(unsigned a, unsigned x, unsigned y) { asm volatile("st.shared.v2.u32 [%0],{%1,%2};" ::"r"(a), "r"(x), "r"(y) : "memory"); }
__device__ __forceinline__ void sts128(unsigned a, unsigned x, unsigned y, unsigned z, unsigned w) { asm volatile("st.shared.v4.u32 [%0],{%1,%2,%3,%4};" ::"r"(a), "r"(x), "r"(y), "r"(z), "r"(w) : "memory"); }
__device__ __forceinline__ unsigned atoms_add(unsigned a, unsigned v) { unsigned o; asm volatile("atom.shared.add.u32 %0,[%1],%2;" : "=r"(o) : "r"(a), "r"(v) : "memory"); return o; }
__device__ __forceinline__ void ldsm4t(unsigned* r, unsigned a) { asm volatile("ldmatrix.sync.aligned.m8n8.x4.trans.shared.b16 {%0,%1,%2,%3},[%4];" : "=r"(r[0]), "=r"(r[1]), "=r"(r[2]), "=r"(r[3]) : "r"(a) : "memory"); }
__device__ __forceinline__ void stsm4t(unsigned a, unsigned r0, unsigned r1, unsigned r2, unsigned r3) { asm volatile("stmatrix.sync.aligned.m8n8.x4.trans.shared.b16 [%0],{%1,%2,%3,%4};" ::"r"(a), "r"(r0), "r"(r1), "r"(r2), "r"(r3) : "memory"); }
__device__ __forceinline__ unsigned pack2(float lo, float hi) { unsigned p; asm("cvt.rn.bf16x2.f32 %0,%1,%2;" : "=r"(p) : "f"(hi), "f"(lo)); return p; }
__device__ __forceinline__ void mma1688(float* d, unsigned a0, unsigned a1, unsigned b0) {
    asm("mma.sync.aligned.m16n8k8.row.col.f32.bf16.bf16.f32 {%0,%1,%2,%3},{%4,%5},{%6},{%7,%7,%7,%7};"
        : "=f"(d[0]), "=f"(d[1]), "=f"(d[2]), "=f"(d[3]) : "r"(a0), "r"(a1), "r"(b0), "f"(0.f));
}
__device__ __forceinline__ void mma16816(float* d, const unsigned* a, unsigned b0, unsigned b1) {
    asm volatile("mma.sync.aligned.m16n8k16.row.col.f32.bf16.bf16.f32 {%0,%1,%2,%3},{%4,%5,%6,%7},{%8,%9},{%10,%10,%10,%10};"
        : "=f"(d[0]), "=f"(d[1]), "=f"(d[2]), "=f"(d[3]) : "r"(a[0]), "r"(a[1]), "r"(a[2]), "r"(a[3]), "r"(b0), "r"(b1), "f"(0.f));
}
__device__ __forceinline__ void tma_x(unsigned da, const void* tm, unsigned ba, int c1) {
    asm volatile("cp.async.bulk.tensor.3d.shared::cluster.global.mbarrier::complete_tx::bytes [%0], [%1, {%3,%4,%3}], [%2];" ::"r"(da), "l"(tm), "r"(ba), "r"(0), "r"(c1) : "memory");
}
__device__ __forceinline__ void tma_2d(unsigned da, const CUtensorMap* tm, unsigned ba, int c0, int c1) {
    asm volatile("cp.async.bulk.tensor.2d.shared::cluster.global.mbarrier::complete_tx::bytes [%0], [%1, {%3,%4}], [%2];" ::"r"(da), "l"(tm), "r"(ba), "r"(c0), "r"(c1) : "memory");
}
__device__ __forceinline__ void tma_st(const CUtensorMap* tm, unsigned sa, int c0, int c1) {
    asm volatile("cp.async.bulk.tensor.2d.global.shared::cta.bulk_group [%0, {%2,%3}], [%1];" ::"l"(tm), "r"(sa), "r"(c0), "r"(c1) : "memory");
}
__device__ __forceinline__ void pf_l2(const void* p, unsigned bytes) { asm volatile("cp.async.bulk.prefetch.L2.global [%0], %1;" ::"l"(p), "r"(bytes) : "memory"); }

#define WG_REGS24(d) "+f"(d[0]), "+f"(d[1]), "+f"(d[2]), "+f"(d[3]), "+f"(d[4]), "+f"(d[5]), "+f"(d[6]), "+f"(d[7]), \
    "+f"(d[8]), "+f"(d[9]), "+f"(d[10]), "+f"(d[11]), "+f"(d[12]), "+f"(d[13]), "+f"(d[14]), "+f"(d[15]), \
    "+f"(d[16]), "+f"(d[17]), "+f"(d[18]), "+f"(d[19]), "+f"(d[20]), "+f"(d[21]), "+f"(d[22]), "+f"(d[23])
template <int NN> __device__ __forceinline__ void wgmma_rs(float* d, const unsigned* a, uint64_t desc, int scale_d);
template <> __device__ __forceinline__ void wgmma_rs<48>(float* d, const unsigned* a, uint64_t desc, int scale_d) {
    asm volatile("{.reg .pred p; setp.ne.b32 p, %29, 0;\n"
        "wgmma.mma_async.sync.aligned.m64n48k16.f32.bf16.bf16 {%0,%1,%2,%3,%4,%5,%6,%7,%8,%9,%10,%11,%12,%13,%14,%15,%16,%17,%18,%19,"
        "%20,%21,%22,%23}, {%24,%25,%26,%27}, %28, p, 1, 1, 0;}"
        : WG_REGS24(d)
        : "r"(a[0]), "r"(a[1]), "r"(a[2]), "r"(a[3]), "l"(desc), "r"(scale_d));
}
template <> __device__ __forceinline__ void wgmma_rs<64>(float* d, const unsigned* a, uint64_t desc, int scale_d) {
    asm volatile("{.reg .pred p; setp.ne.b32 p, %37, 0;\n"
        "wgmma.mma_async.sync.aligned.m64n64k16.f32.bf16.bf16 {%0,%1,%2,%3,%4,%5,%6,%7,%8,%9,%10,%11,%12,%13,%14,%15,%16,%17,%18,%19,"
        "%20,%21,%22,%23,%24,%25,%26,%27,%28,%29,%30,%31}, {%32,%33,%34,%35}, %36, p, 1, 1, 0;}"
        : WG_REGS24(d), "+f"(d[24]), "+f"(d[25]), "+f"(d[26]), "+f"(d[27]), "+f"(d[28]), "+f"(d[29]), "+f"(d[30]), "+f"(d[31])
        : "r"(a[0]), "r"(a[1]), "r"(a[2]), "r"(a[3]), "l"(desc), "r"(scale_d));
}
__device__ __forceinline__ void wg_fence() { asm volatile("wgmma.fence.sync.aligned;" ::: "memory"); }
__device__ __forceinline__ void wg_commit() { asm volatile("wgmma.commit_group.sync.aligned;" ::: "memory"); }
__device__ __forceinline__ void wg_wait0() { asm volatile("wgmma.wait_group.sync.aligned 0;" ::: "memory"); }

#define PF(D, RW, K, J0, J1) \
    "cvt.rn.bf16x2.f32 t0, " #D "1, " #D "0;\n cvt.rn.bf16x2.f32 t1, " #D "3, " #D "2;\n" \
    "mov.b32 {lo, hi}, " #RW ";\n mov.b32 u0, {lo, lo};\n mov.b32 u1, {hi, hi};\n" \
    "fma.rn.bf16x2 a" #K "_" #J0 ", t0, u0, a" #K "_" #J0 ";\n fma.rn.bf16x2 a" #K "_" #J1 ", t1, u1, a" #K "_" #J1 ";\n"
#define MMA(D, A0, A1) "mma.sync.aligned.m16n8k8.row.col.f32.bf16.bf16.f32 {" #D "0," #D "1," #D "2," #D "3}, {" #A0 "," #A1 "}, {bf}, {fz,fz,fz,fz};\n"
#define LDX(X, OFF) "ldmatrix.sync.aligned.m8n8.x4.trans.shared.b16 {" #X "0," #X "1," #X "2," #X "3}, [xa+" STR(SM_X) "+" #OFF "];\n"
#define DECODE \
    "lop3.b32 xa, dn, 0x3F800, %1, 0xEA;\n" \
    "shr.u32 t2, dn, 21;\n mad.lo.u32 ra, t2, 32, %2;\n mad.lo.u32 ca, t2, 32, %3;\n" \
    "and.b32 t3, dn, 0x7FF;\n shl.b32 t3, t3, 2;\n" SETD
#define LOADS \
    LDX(x, 0) "@act ld.shared.u32 bf, [ca+" STR(SM_R) "];\n" LDX(y, 512) LDR(r, 0) \
    "ld.shared.u32 dn, [t3+" STR(SM_NEXT) "];\n"
#if DISP == 0
#define SETD "bfe.u32 ix, dn, 18, 3;\n"
#define DISPATCH "brx.idx.uni ix, TS;\n"
#define T23
#define T45
#else
#define SETD "and.b32 ix, dn, 0x40000;\n setp.ne.u32 q0, ix, 0;\n and.b32 ix, dn, 0x80000;\n setp.ne.u32 q1, ix, 0;\n and.b32 ix, dn, 0x100000;\n setp.ne.u32 q2, ix, 0;\n"
#define DISPATCH "@q2 bra.uni T45;\n @q1 bra.uni T23;\n @q0 bra.uni B1;\n bra.uni B0;\n"
#define T23 "T23:\n @q0 bra.uni B3;\n"
#define T45 "T45:\n @q1 bra.uni FIN;\n @q0 bra.uni B5;\n"
#endif
#define LDR(R, OFF) "ld.shared.v4.u32 {" #R "0," #R "1," #R "2," #R "3}, [ra+" STR(SM_R) "+" #OFF "];\n"
#ifdef JG
#define JIG "and.b32 t0, t0, 0xFFFF;\n"
#else
#define JIG
#endif
#define BODY(K) "B" #K ":\n" \
    MMA(d, x0, x1) MMA(e, x2, x3) LDX(x, 1024) "and.b32 bn, dn, 0x7F8;\n" \
    "mbarrier.test_wait.parity.shared::cta.b64 p, [bn+" STR(SM_FULL) "], 0;\n" \
    PF(d, r0, K, 0, 1) MMA(d, y0, y1) PF(e, r1, K, 2, 3) MMA(e, y2, y3) LDX(y, 1536) LDR(s, 128) \
    PF(d, r2, K, 4, 5) MMA(d, x0, x1) PF(e, r3, K, 6, 7) MMA(e, x2, x3) \
    PF(d, s0, K, 8, 9) MMA(d, y0, y1) \
    "@l0 mbarrier.arrive.shared::cta.b64 _, [bc+" STR(SM_EMPTY) "];\n" \
    PF(e, s1, K, 10, 11) MMA(e, y2, y3) \
    "mov.u32 bc, bn;\n" DECODE \
    "@!p bra.uni W" #K ";\n" \
    "R" #K ":\n" LOADS \
    PF(d, s2, K, 12, 13) PF(e, s3, K, 14, 15) DISPATCH
#ifdef DBG_TR
#define SM_TR (SM_NEXT + CAPP * 4)
#define TRC "mov.u32 t1, %%clock;\n st.shared.u32 [bc+" STR(SM_TR) "], t1;\n"
extern "C" { __device__ unsigned g_trace[NCTA * 4 * 180]; }
#else
#define TRC
#endif
#define WAIT(K) "W" #K ":\n mov.u32 t0, 0;\n" \
    "V" #K ":\n mbarrier.try_wait.parity.shared::cta.b64 p, [bc+" STR(SM_FULL) "], 0;\n" TRC "@p bra.uni R" #K ";\n" \
    "add.u32 t0, t0, 1;\n setp.lt.u32 p, t0, 400000;\n @p bra.uni V" #K ";\n bra.uni R" #K ";\n"
#define Z4(K, A, B, C, D) "mov.u32 a" #K "_" #A ", 0; mov.u32 a" #K "_" #B ", 0; mov.u32 a" #K "_" #C ", 0; mov.u32 a" #K "_" #D ", 0;\n"
#define ZACC(K) Z4(K, 0, 1, 2, 3) Z4(K, 4, 5, 6, 7) Z4(K, 8, 9, 10, 11) Z4(K, 12, 13, 14, 15)
#define ST4(K, A, B, C, D, R, P) "stmatrix.sync.aligned.m8n8.x4.trans.shared.b16 [" #R "+" STR(SM_H) "+" #K "*512+" #P "*" STR(HPANEL) "], {a" #K "_" #A ",a" #K "_" #B ",a" #K "_" #C ",a" #K "_" #D "};\n"
#define STP(P, A, B, C, D, R0, R1) ST4(0, A, B, C, D, R0, P) ST4(1, A, B, C, D, R1, P) ST4(2, A, B, C, D, R0, P) ST4(3, A, B, C, D, R1, P) \
    "@q0 bra.uni E" #P ";\n" ST4(4, A, B, C, D, R0, P) ST4(5, A, B, C, D, R1, P) "E" #P ":\n"
#define FS(P) "add.u32 t2, bn, " STR(SM_H) "-" STR(SM_X) "+" #P "*" STR(HPANEL) ";\n shr.u32 t2, t2, 14;\n mad.lo.u32 t2, t2, 8, bc;\n"
#define FW(ID, PRE, A) "@q1 bra.uni G" #ID ";\n" PRE "mov.u32 t3, 0;\n" \
    "F" #ID ":\n mbarrier.try_wait.parity.shared::cta.b64 p, [" #A "+" STR(SM_EMPTY) "-8*" STR(NX) "], 0;\n vote.sync.all.pred p, p, -1;\n" \
    "add.u32 t3, t3, 1;\n setp.lt.and.u32 p, t3, 400000, !p;\n @p bra.uni F" #ID ";\n G" #ID ":\n"
__device__ __forceinline__ unsigned consumer(unsigned head) {
    const int lane = threadIdx.x & 31, g = lane >> 2, t = lane & 3;
    const unsigned xl = (lane & 3) * 128 + ((((lane >> 3) + (lane & 4)) ^ (lane & 3)) << 4);
    const unsigned rl = (t >> 1) * 320 + g * 16;
    const unsigned cl = (t >> 1) == (g >> 2) ? 256 + (2 * (g & 3) + (t & 1)) * 4 : 0;
    asm volatile("{\n"
        ".reg .b32 a0_<16>, a1_<16>, a2_<16>, a3_<16>, a4_<16>, a5_<16>;\n"
        ".reg .b32 x<4>, y<4>, r<4>, s<4>, t<4>, u<2>, bf, xa, ra, ca, bn, bc, dn, ix;\n"
        ".reg .f32 d<4>, e<4>, fz;\n .reg .b16 lo, hi;\n .reg .pred p, q<3>, act, l0;\n"
#if DISP == 0
        "TS: .branchtargets B0, B1, B2, B3, B4, B5, FIN, FIN;\n"
#endif
        "mov.f32 fz, 0f00000000;\n mov.u32 bf, 0;\n setp.ne.u32 act, %3, 0;\n setp.eq.u32 l0, %1, 0;\n mov.u32 dn, %0;\n"
        ZACC(0) ZACC(1) ZACC(2) ZACC(3) ZACC(4) ZACC(5)
        "and.b32 bc, dn, 0x7F8;\n"
        DECODE "and.b32 t0, dn, 0x1C0000;\n setp.eq.u32 p, t0, 0x1C0000;\n @p bra.uni FIN;\n"
        WAIT(6)
        "R6:\n" LOADS DISPATCH
        BODY(0) BODY(1) T23 BODY(2) BODY(3) T45 BODY(4) BODY(5)
        WAIT(0) WAIT(1) WAIT(2) WAIT(3) WAIT(4) WAIT(5)
        "FIN:\n mov.u32 bc, " STR(SM_MISC) ";\n ld.shared.u32 bc, [bc+88];\n add.u32 bc, bc, 7;\n and.b32 bc, bc, -8;\n"
        "mov.u32 t2, %%laneid;\n min.u32 ca, t2, " STR(NX) "-1;\n mad.lo.u32 ca, ca, 8, bc;\n"
        "mbarrier.test_wait.parity.shared::cta.b64 p, [ca+" STR(SM_EMPTY) "-8*" STR(NX) "], 0;\n vote.sync.all.pred q1, p, -1;\n"
        "sub.u32 t0, ra, %2;\n" JIG "shr.u32 %0, t0, 5;\n mul.lo.u32 bn, t0, 96;\n"
        "add.u32 t0, bn, %1;\n xor.b32 t1, t0, 64;\n setp.eq.u32 q0, %0, 12;\n vote.sync.all.pred q0, q0, -1;\n and.b32 t2, t2, 1;\n mad.lo.u32 bn, t2, 3071, bn;\n"
        FW(0, FS(0), t2) STP(0, 0, 1, 2, 3, t0, t1) FW(1, FS(1), t2) STP(1, 4, 5, 6, 7, t1, t0) FW(2, , ca)
#ifdef DBG_TIMES
        "mov.u32 t2, %%clock;\n or.b32 t2, t2, 1;\n mov.u32 t3, " STR(SM_BITS) ";\n st.shared.u32 [t3+36], t2;\n"
#endif
        STP(2, 8, 9, 10, 11, t0, t1) STP(3, 12, 13, 14, 15, t1, t0)
        "}\n" : "+r"(head) : "r"(xl), "r"(rl), "r"(cl) : "memory");
    return head;
}

#define RMMA(D, Q, B0, B1) "mma.sync.aligned.m16n8k16.row.col.f32.bf16.bf16.f32 {" #D "0," #D "1," #D "2," #D "3}, {w" #Q "_0,w" #Q "_1,w" #Q "_2,w" #Q "_3}, {" #B0 "," #B1 "}, {fz,fz,fz,fz};\n"
#define RPK(I, D) "cvt.rn.bf16x2.f32 u" #I ", " #D "2, " #D "0;\n cvt.rn.bf16x2.f32 v" #I ", " #D "3, " #D "1;\n"
#define RG(Q0, Q1, Q2, Q3, B0, B1, A, OFF) \
    RMMA(da, Q0, B0, B1) RMMA(db, Q1, B0, B1) RMMA(dc, Q2, B0, B1) RMMA(dd, Q3, B0, B1) \
    RPK(0, da) RPK(1, db) RPK(2, dc) RPK(3, dd) \
    "st.shared.v4.u32 [" #A "+" #OFF "], {u0,u1,u2,u3};\n st.shared.v4.u32 [" #A "+" #OFF "+4*" STR(RSTR) "], {v0,v1,v2,v3};\n"
#define RSPLIT(M) "setp.eq.u32 pk, ro, " #M ";\n @pk exit;\n"
#if RSPL & 2
#define RS1 RSPLIT(1)
#else
#define RS1
#endif
#if RSPL & 4
#define RS2 RSPLIT(2)
#else
#define RS2
#endif
#if RSPL & 8
#define RS3 RSPLIT(3)
#else
#define RS3
#endif
#ifdef NOLOAD
#define RTX "0"
#else
#define RTX "16384"
#endif
#ifdef DBG_R
#define RW0 "mov.u32 tw, %%clock;\n"
#define RW1 "mov.u32 t0, %%clock;\n sub.u32 t0, t0, tw;\n add.u32 %0, %0, t0;\n"
#else
#define RW0
#define RW1
#endif
#ifdef XREC
#define RG2(B0, B1)
#else
#define RG2(B0, B1) RG(8, 9, 10, 11, B0, B1, a0, 128) RS3 RG(12, 13, 14, 15, B0, B1, a0, 448)
#endif
#define RSTAGE(ID, B0, B1, SEL, PRE, MID) \
    "@!pw bra.uni RW" #ID ";\n RR" #ID ":\n" PRE \
    "mbarrier.test_wait.parity.shared::cta.b64 pw, [sb+" STR(SM_EMPTY) "+16-8*" STR(NR) "], 0;\n" \
    "add.u32 a0, ro, %2;\n add.u32 a2, ro, %4;\n" \
    RG(0, 1, 2, 3, B0, B1, a0, 0) RS1 RG(4, 5, 6, 7, B0, B1, a0, 320) RS2 MID \
    "selp.b32 t0, " SEL ", pe;\n" \
    "mma.sync.aligned.m16n8k8.row.col.f32.bf16.bf16.f32 {da0,da1,da2,da3}, {%5,%6}, {t0}, {fz,fz,fz,fz};\n" RPK(0, da) \
    "st.shared.u32 [a2], u0;\n st.shared.u32 [a2+4*" STR(RSTR) "], v0;\n" \
    RG2(B0, B1) \
    "bar.warp.sync 0xffffffff;\n elect.sync _|l0, 0xffffffff;\n" \
    "@l0 mbarrier.arrive.expect_tx.shared::cta.b64 _, [sb+" STR(SM_FULL) "], " RTX ";\n" \
    "add.u32 sb, sb, 16;\n add.u32 ro, ro, 16*" STR(RSTR) ";\n setp.ge.u32 pk, ro, " STR(SM_EID) ";\n @pk sub.u32 ro, ro, 8*" STR(NR) "*" STR(RSTR) ";\n" \
    "setp.ge.u32 pk, sb, %9;\n @pk bra.uni REND;\n"
#define RWAIT(ID) "RW" #ID ":\n" RW0 "mov.u32 t1, 0;\n" \
    "RV" #ID ":\n mbarrier.try_wait.parity.shared::cta.b64 pk, [sb+" STR(SM_EMPTY) "-8*" STR(NR) "], 0;\n" \
    "add.u32 t1, t1, 1;\n setp.lt.and.u32 pk, t1, 400000, !pk;\n @pk bra.uni RV" #ID ";\n" RW1 "bra.uni RR" #ID ";\n"
#define RLD1(S, I, J, E) "shl.b32 " #E ", " #E ", 2;\n lop3.b32 " #E ", " #E ", 0xFFFFC, tt, 0xEA;\n mad.wide.u32 ad, " #E ", 8, %10;\n " RLDG ".v2.u32 {" #S #I "," #S #J "}, [ad];\n"
#define RLD2(S, I, E, F) "selp.b32 t1, " #E ", " #F ", pe;\n and.b32 t1, t1, -2;\n mad.wide.u32 ad, t1, 2, %11;\n " RLDG ".u32 " #S #I ", [ad];\n"
#define RLOAD(S, DEP) "lop3.b32 tt, " #DEP ", %12, %7, 0xEA;\n" \
    RLD1(S, 0, 1, e0) RLD1(S, 2, 3, e1) RLD2(S, 8, e0, e1) RLD1(S, 4, 5, e2) RLD1(S, 6, 7, e3) RLD2(S, 9, e2, e3)
#define REID1(I) "ld.shared.u32 e" #I ", [ea+" STR(SM_EID) "+64*" #I "];\n"
#define REID REID1(0) REID1(1) REID1(2) REID1(3) "add.u32 ea, ea, 256;\n"
#define RPF "mad.wide.u32 ad, pf, 4096, %14;\n add.u32 pf, pf, 2*" STR(NCTA) ";\n setp.lt.u32 pk, pf, %3;\n selp.b32 pf, pf, %3, pk;\n" \
    "elect.sync _|l0, 0xffffffff;\n @l0 cp.async.bulk.prefetch.L2.global [ad], 4096;\n"
#define RLDW(Q) "ldmatrix.sync.aligned.m8n8.x4.trans.shared.b16 {w" #Q "_0,w" #Q "_1,w" #Q "_2,w" #Q "_3}, [%1+2*(64*(2*(" #Q ">>3)+((" #Q "&3)>>1))+8*((2*(" #Q "&1)+(" #Q "&4))^(2*(" #Q "&2))))];\n"
__device__ __forceinline__ unsigned recorder(const Params& p, int hw, int nst, unsigned cg0, unsigned cg1) {
    const int lane = threadIdx.x & 31, g = lane >> 2, t = lane & 3, mi = lane >> 3, r = lane & 7;
    const unsigned wa = SM_WR + (4 * (r >> 1) + (r & 1) + 2 * (mi >> 1)) * 528 + (mi & 1) * 16;
    unsigned ewait = 0;
    asm volatile("{\n"
        ".reg .b32 w0_<4>, w1_<4>, w2_<4>, w3_<4>, w4_<4>, w5_<4>, w6_<4>, w7_<4>, w8_<4>, w9_<4>, w10_<4>, w11_<4>, w12_<4>, w13_<4>, w14_<4>, w15_<4>;\n"
        ".reg .b32 x<10>, y<10>, e<4>, u<4>, v<4>, a<3>, t<2>, tt, tw, ea, sb, ro, pf;\n .reg .b64 ad;\n"
        ".reg .f32 da<4>, db<4>, dc<4>, dd<4>, fz;\n .reg .pred pw, pk, pe, l0;\n"
        RLDW(0) RLDW(1) RLDW(2) RLDW(3) RLDW(4) RLDW(5) RLDW(6) RLDW(7) RLDW(8) RLDW(9) RLDW(10) RLDW(11) RLDW(12) RLDW(13) RLDW(14) RLDW(15)
        "mov.f32 fz, 0f00000000;\n and.b32 t0, %7, 1;\n setp.eq.u32 pe, t0, 0;\n"
        "mov.u32 pf, %15;\n mad.lo.u32 ea, %13, 32, %8;\n shl.b32 sb, %13, 3;\n mad.lo.u32 ro, %13, 8*" STR(RSTR) ", " STR(SM_R) ";\n"
        "bar.sync 0, 512;\n"
        "setp.lt.u32 pw, sb, %9;\n @!pw bra.uni REND;\n"
        REID RLOAD(x, %12) REID
        "RTOP:\n"
        RSTAGE(0, x0, x1, "x8, 0", RLOAD(y, x0), ) RSTAGE(1, x2, x3, "0, x8", , ) RSTAGE(2, x4, x5, "x9, 0", , RPF) RSTAGE(3, x6, x7, "0, x9", , REID)
        RSTAGE(4, y0, y1, "y8, 0", RLOAD(x, y0), ) RSTAGE(5, y2, y3, "0, y8", , ) RSTAGE(6, y4, y5, "y9, 0", , RPF) RSTAGE(7, y6, y7, "0, y9", , REID)
        "bra.uni RTOP;\n"
        RWAIT(0) RWAIT(1) RWAIT(2) RWAIT(3) RWAIT(4) RWAIT(5) RWAIT(6) RWAIT(7)
        "REND:\n and.b32 t0, sb, 8;\n and.b32 %0, %0, -16;\n or.b32 %0, %0, t0;\n}\n"
        : "+r"(ewait)
        : "r"(wa), "r"(t * RSTR + g * 16), "r"(p.N / 2 - 1), "r"(t * RSTR + 256 + g * 4), "r"(cg0), "r"(cg1), "r"(t),
          "r"(((g >> 1) + 4 * (g & 1)) * 4), "r"(nst * 8), "l"(p.ea), "l"(p.sh), "r"(p.zero), "r"(hw), "l"(p.x),
          "r"(min((int)blockIdx.x + (PFLEAD / 2 + hw) * NCTA, p.N / 2 - 1)) : "memory");
    return ewait;
}
#ifdef NOLOAD
#define TROW(J, Z0, Z1)
#else
#define TROW(J, Z0, Z1) "@l0 cp.async.bulk.tensor.3d.shared::cluster.global.mbarrier::complete_tx::bytes [xs+" STR(SM_X) "+" #J "*2048], [mp, {" #Z0 ",k" #J "," #Z1 "}], [mb];\n"
#endif
#ifdef DBG_H
#define TL "add.u32 %0, %0, c;\n"
#else
#define TL
#endif
#ifndef TCLK
#define TCLK "mov.u64 ad, %%clock64;\n cvt.u32.u64 c, ad;\n"
#endif
#define TDL "mul.hi.u32 dl, q1, rt;\n add.u32 dl, dl, %4;\n shr.u32 q0, q0, 18;\n shr.u32 q1, q1, 18;\n shr.u32 q2, q2, 18;\n shr.u32 q3, q3, 18;\n"
__device__ __forceinline__ unsigned issuer(const CUtensorMap* tm, const Params& p, int nst, unsigned T0) {
    unsigned late = 0;
    asm volatile("{\n"
        ".reg .b32 k<4>, q<4>, z<8>, xs, sa, sb, mb, dl, c, n, rt;\n .reg .b64 ad, mp;\n .reg .pred pw, pk, l0;\n"
        "mov.u32 n, " STR(SM_NEXT) ";\n ld.shared.v4.u32 {z0,z1,z2,z3}, [n+-32];\n ld.shared.v4.u32 {z4,z5,z6,z7}, [n+-16];\n"
        "ld.shared.u64 ad, [n+-48];\n add.u64 mp, ad, %1;\n ld.shared.u32 rt, [n+-40];\n add.u32 rt, rt, %5;\n"
        "mov.u32 sa, 0;\n mov.u32 xs, %2;\n mov.u32 sb, 0;\n"
        "ld.shared.v4.u32 {q0,q1,q2,q3}, [sa+" STR(SM_EID) "];\n" TDL "bra.uni TW;\n"
        "TR:\n" TL
        "elect.sync _|l0, 0xffffffff;\n"
        "shl.b32 k0, q0, 2;\n shl.b32 k1, q1, 2;\n shl.b32 k2, q2, 2;\n shl.b32 k3, q3, 2;\n add.u32 mb, sb, " STR(SM_FULL) ";\n"
        "add.u32 sa, sa, 16;\n ld.shared.v4.u32 {q0,q1,q2,q3}, [sa+" STR(SM_EID) "];\n"
        "shr.u32 sb, sa, 2;\n and.b32 sb, sb, -8;\n"
        "mbarrier.test_wait.parity.shared::cta.b64 pw, [sb+" STR(SM_EMPTY) "-8*" STR(NX) "], 0;\n"
        TROW(0, z0, z1) TROW(1, z2, z3) TROW(2, z4, z5) TROW(3, z6, z7) TCLK TDL
        "sub.u32 c, c, dl;\n setp.lt.and.u32 pw, sb, %3, pw;\n setp.ge.and.s32 pw, c, 0, pw;\n"
        "add.u32 xs, xs, 8192;\n setp.eq.u32 pk, xs, " STR(SM_R) "-" STR(SM_X) ";\n selp.b32 xs, 0, xs, pk;\n"
        "@pw bra.uni TR;\n"
        "TW:\n setp.ge.u32 pk, sb, %3;\n @pk bra.uni TEND;\n mov.u32 n, 0;\n"
        "TV:\n mbarrier.try_wait.parity.shared::cta.b64 pk, [sb+" STR(SM_EMPTY) "-8*" STR(NX) "], 0;\n"
        "add.u32 n, n, 1;\n setp.lt.and.u32 pk, n, 400000, !pk;\n @pk bra.uni TV;\n"
        "TS:\n" TCLK "sub.u32 c, c, dl;\n setp.lt.s32 pk, c, 0;\n @pk bra.uni TS;\n bra.uni TR;\n"
        "TEND:\n}\n"
        : "+r"(late)
        : "l"(tm), "r"(((NX - nst % NX) % NX) * 16384), "r"(nst * 8), "r"(T0), "r"(p.rate)
#ifdef DBG_TR
          , "l"(g_trace + blockIdx.x * 720)
#endif
        : "memory");
    return late;
}

__device__ __forceinline__ void slow_path(const Params& p) {
    const int lane = threadIdx.x & 31, warp = threadIdx.x >> 5;
#pragma unroll 1
    for (int nl = warp; nl < NPC; nl += 16) {
        const int node = blockIdx.x * NPC + nl;
        float acc[4][8];
#pragma unroll
        for (int w = 0; w < 4; w++)
#pragma unroll
            for (int j = 0; j < 8; j++) acc[w][j] = 0.f;
        if (node < p.N) {
#pragma unroll 1
            for (int e0 = 0; e0 < p.E; e0 += 32) {
                int e = e0 + lane;
                unsigned m = __ballot_sync(~0u, e < p.E && p.dst[e] == node);
                while (m) {
                    int ee = e0 + __ffs(m) - 1; m &= m - 1;
                    int s = p.src[ee];
                    float rw[8];
#pragma unroll
                    for (int j = 0; j < 8; j++) rw[j] = 0.f;
#pragma unroll 1
                    for (int k = 0; k < 16; k++) {
                        float a = __bfloat162float(p.ea[(size_t)ee * 16 + k]);
#pragma unroll
                        for (int j = 0; j < 8; j++) rw[j] += a * __bfloat162float(p.wr[k * 256 + lane * 8 + j]);
                    }
#pragma unroll 1
                    for (int u = 0; u < 4; u++) {
                        float y[8];
#pragma unroll
                        for (int j = 0; j < 8; j++) y[j] = rw[j] * __bfloat162float(p.x[((size_t)s * 4 + u) * 256 + lane * 8 + j]);
#pragma unroll
                        for (int w = 0; w < 4; w++) {
                            float a = 0.f;
#pragma unroll
                            for (int v = 0; v < 4; v++) a += __bfloat162float(p.cg[u * 16 + v * 4 + w]) * __bfloat162float(p.sh[(size_t)ee * 4 + v]);
#pragma unroll
                            for (int j = 0; j < 8; j++) acc[w][j] += a * y[j];
                        }
                    }
                }
            }
        }
#pragma unroll
        for (int w = 0; w < 4; w++) {
            int R = nl * 4 + w;
            sts128(SM_H + (lane >> 3) * HPANEL + R * 128 + (((lane & 7) ^ (R & 7)) << 4),
                   pack2(acc[w][0], acc[w][1]), pack2(acc[w][2], acc[w][3]), pack2(acc[w][4], acc[w][5]), pack2(acc[w][6], acc[w][7]));
        }
    }
}

template <int NN>
__device__ __forceinline__ void out_chunk(float* d, unsigned stg, const CUtensorMap* tmo, int wg, int row0, bool first, unsigned a, bool lead) {
    if (!first) {
        if (lead) asm volatile("cp.async.bulk.wait_group.read 0;" ::: "memory");
    }
    asm volatile("bar.sync %0, 128;" ::"r"(wg + 1) : "memory");
#pragma unroll
    for (int n = 0; n < NN / 8; n += 2)
        stsm4t(a + n * 1024, pack2(d[4 * n], d[4 * n + 1]), pack2(d[4 * n + 2], d[4 * n + 3]), pack2(d[4 * n + 4], d[4 * n + 5]), pack2(d[4 * n + 6], d[4 * n + 7]));
    fence_async();
    asm volatile("bar.sync %0, 128;" ::"r"(wg + 1) : "memory");
    if (lead) {
#pragma unroll
        for (int j = 0; j < NN / 16; j++) tma_st(tmo, stg + j * 2048, wg * 64, row0 + j * 16);
        asm volatile("cp.async.bulk.commit_group;" ::: "memory");
    }
}

__global__ void __launch_bounds__(512, 1)
mace_kernel(const __grid_constant__ Params p, const __grid_constant__ CUtensorMap tmx, const __grid_constant__ CUtensorMap tmw,
            const __grid_constant__ CUtensorMap tmo) {
    extern __shared__ __align__(1024) char smem_raw[];
    const unsigned tstart = clk();
    const int tid = threadIdx.x, cta = blockIdx.x;
    const int e0 = cta * EPC + tid * 4;
    const bool has = tid < EPC / 4 && e0 < p.Ef;
    uint4 s4, d4;
    asm volatile("{.reg .pred q; setp.ne.u32 q, %10, 0;\n @q ld.global.nc.v4.u32 {%0,%1,%2,%3}, [%8];\n @q ld.global.nc.v4.u32 {%4,%5,%6,%7}, [%9];}"
        : "=r"(d4.x), "=r"(d4.y), "=r"(d4.z), "=r"(d4.w), "=r"(s4.x), "=r"(s4.y), "=r"(s4.z), "=r"(s4.w) : "l"(p.dst + e0), "l"(p.src + e0), "r"((int)has) : "memory");
    const int lane = tid & 31, warp = __shfl_sync(~0u, tid >> 5, 0);
    const unsigned wbar = SM_MISC, totA = SM_MISC + 80;
    bool slow = p.Ef == 0;
    int total = 0, nst = 0;
    unsigned T0 = 0, cg0 = 0, cg1 = 0, dsc[4];
    if (slow) {
        if (tid < 8) bar_init(wbar + tid * 8, 1);
    } else if (warp >= NXT / 32) {
        unsigned* const ctr = (unsigned*)(p.xch + NCTA * NCTA * NCH);
        unsigned epn;
        if (warp == 15) {
            asm volatile("ld.relaxed.gpu.global.u32 %0, [%1];" : "=r"(epn) : "l"(ctr));
        } else {
#pragma unroll
            for (int k = 0; k < 6; k++) {
                const unsigned i = lane + k * 32, c = i < CAPP / 16 + 8 || i >= CAPP / 8 + 8 ? 0xFFFFFu : 0xFFFF8u;
                sts128(i < CAPP / 8 + 8 ? SM_FULL + i * 16 : wbar + (i - CAPP / 8 - 8) * 16, c << 1, c << 11, c << 1, c << 11);
            }
            fence_async();
            __syncwarp();
            if (lane < 16) asm volatile("mbarrier.arrive.shared::cta.b64 _, [%0];" ::"r"(SM_EMPTY + (lane - 16) * 8) : "memory");
        }
        uint4 w4[8];
        unsigned c4[4];
#pragma unroll
        for (int k = 0; k < 8; k++) asm volatile("ld.global.nc.v4.u32 {%0,%1,%2,%3}, [%4];" : "=r"(w4[k].x), "=r"(w4[k].y), "=r"(w4[k].z), "=r"(w4[k].w) : "l"((const uint4*)p.wr + (tid - NXT + k * 64)));
#pragma unroll
        for (int k = 0; k < 4; k++) asm volatile("ld.global.nc.u16 %0, [%1];" : "=r"(c4[k]) : "l"(p.cg + (lane & 4) * 8 + (lane & 2) * 4 + (lane >> 3) + (k & 1) * 4 + (k & 2) * 8));
        auto put = [&]() {
#pragma unroll
            for (int k = 0; k < 8; k++) sts128(SM_WR + (warp - NXT / 32 + 2 * k) * 528 + lane * 16, w4[k].x, w4[k].y, w4[k].z, w4[k].w);
            asm volatile("prmt.b32 %0, %2, %3, 0x5410;\n prmt.b32 %1, %4, %5, 0x5410;" : "=&r"(cg0), "=r"(cg1) : "r"(c4[0]), "r"(c4[1]), "r"(c4[2]), "r"(c4[3]));
        };
        if (warp == 15) {
            epn = (epn | 255) + 1;
            sts64(totA, epn, 0);
            narrive<7, NXT + 32>();
            nsync<10, NXT + 32>();
            if (lane == 0) asm volatile("red.relaxed.gpu.global.add.u32 [%0], %1;" ::"l"(ctr), "r"(cta ? 1 : 257 - NCTA) : "memory");
            put();
            while (clk() - tstart < POLLT);
            unsigned v; int it = 0;
            do asm volatile("ld.relaxed.gpu.global.u32 %0, [%1];" : "=r"(v) : "l"(ctr) : "memory");
            while (v != epn && ++it < 4096);
            narrive<8, NXT + 32>();
#ifdef DBG_PRO
            sts32(totA + 16, it * 2);
#endif
            nsync<9, NXT + 32>();
            uint4 u[NBW];
#pragma unroll
            for (int q = 0; q < NBW; q++) u[q] = lds128(SM_BKT + (lane * NBW + q) * 16);
            const unsigned mx = lds32(SM_CNT + min(lane, NXT / 32 - 1) * 4), bad = lds32(totA + 4);
            unsigned sum = 0;
#pragma unroll
            for (int q = 0; q < NBW; q++) sum += u[q].x + u[q].y + u[q].z + u[q].w;
            unsigned inc = sum;
#pragma unroll
            for (int o = 1; o < 32; o <<= 1) asm volatile("{.reg .pred q; .reg .b32 t; shfl.sync.up.b32 t|q, %0, %1, 0, -1;\n @q add.u32 %0, %0, t;}" : "+r"(inc) : "r"(o));
            sum = inc - sum;
#pragma unroll
            for (int q = 0; q < NBW; q++) {
                const unsigned a2 = sum + u[q].x + u[q].y;
                sts128(SM_BKT + (lane * NBW + q) * 16, sum, sum + u[q].x, a2, a2 + u[q].z);
                sum = a2 + u[q].z + u[q].w;
            }
            const unsigned t0 = tstart + ((__reduce_max_sync(~0u, mx) & 0xFFF8) << 1) + T0DELTA;
            if (lane == 31) sts64(totA + 8, (inc >> 2) + bad, t0);
        } else {
            if (elect()) {
                asm volatile("prefetch.tensormap [%0];" ::"l"(&tmx) : "memory");
                asm volatile("prefetch.tensormap [%0];" ::"l"(&tmw) : "memory");
                asm volatile("prefetch.tensormap [%0];" ::"l"(&tmo) : "memory");
                if (cta < 128) pf_l2(p.wo + cta * 512, 1024);
            }
            put();
#pragma unroll
            for (int i = 0; i < PFLEAD / 2; i++) {
                if (i == PF1) while (clk() - tstart < PFT);
                if (elect()) pf_l2(p.x + (size_t)min(i * NCTA + cta, p.N / 2 - 1) * 2048, 4096);
            }
        }
        cta_sync();
        total = __shfl_sync(~0u, lds32(totA + 8), 0);
        slow = total > CAP;
        nst = (total + 7) >> 3;
    } else {
        {
            const unsigned du = DUM + (((cta * NCH + tid) & 31) << (18 + BSH));
#pragma unroll
            for (int k = 0; k < 3; k++) sts128(SM_STAGE + (tid + k * NXT) * 16, du, du, du, ~0u);
            if (tid < NCTA) sts32(SM_CNT + tid * 4, 0);
        }
        TK(24, e0);
        nsync<6, NXT>();
        TK(0, e0);
        const bool h2 = tid < NCTA * NCH - 2 * NXT;
        unsigned cc[3];
        const char* xo[3];
#pragma unroll
        for (int k = 0; k < 3; k++) {
            const unsigned i = tid + k * NXT;
            cc[k] = (i * 6554) >> 16;
            xo[k] = pin64((const char*)(p.xch + (cc[k] * ((NCTA - 1) * NCH) + cta * NCH + i)));
        }
        TK(26, d4.x);
        if (has) {
            const unsigned ss[4] = {s4.x, s4.y, s4.z, s4.w}, dd[4] = {d4.x, d4.y, d4.z, d4.w};
            unsigned c[4], o[4];
#pragma unroll
            for (int j = 0; j < 4; j++) { c[j] = __umulhi(dd[j], 0xFFFFFFFFu / NPC + 1); o[j] = atoms_add(SM_CNT + c[j] * 4, 0x15558); }
#pragma unroll
            for (int j = 0; j < 4; j++) {
                const unsigned dl = dd[j] - c[j] * NPC;
                sts32(SM_STAGE + (c[j] * (NCH * 4) + min(o[j] >> 16, NCH * 4 - 1)) * 4, (ss[j] << 18) + (tid * 4 + j) + dl * 2048 + (dl * 43 >> 8) * 4096);
            }
        }
        TK(28, e0);
        nsync<7, NXT + 32>();
        TK(1, e0);
        const unsigned ep = (lds32(totA) << 8) | 0x80000000u;
        {
            const unsigned tag = ep | (min((clk() - tstart) >> 4, 0x1FFFu) << 3);
            uint4 v[3];
#pragma unroll
            for (int k = 0; k < 3; k++) v[k] = lds128(SM_STAGE + (tid + k * NXT) * 16);
#pragma unroll
            for (int k = 0; k < 3; k++)
                if (k < 2 || h2) asm volatile(XST " [%0], {%1,%2,%3,%4};" ::"l"(xo[k]), "r"(v[k].x), "r"(v[k].y), "r"(v[k].z), "r"(tag + (v[k].w != ~0u)) : "memory");
        }
        narrive<10, NXT + 32>();
        TK(16, e0);
        if ((unsigned)__cvta_generic_to_shared(smem_raw) != SB) __trap();
        if (tid < NBW * 32 + 8) { const unsigned v = tid < NBW * 32 ? 0 : CAP * 4; sts128(SM_BKT + tid * 16, v, v, v, v); }
        if (tid < 384) { const unsigned v = tid < 381 ? (p.N - 1) << 18 : 0; sts128(SM_EID + tid * 16, v, v, v, v); }
        if (tid < 1392 / 4) sts128(SM_SRC + tid * 16, NCONS << 14, NCONS << 14, NCONS << 14, NCONS << 14);
        if (tid < 159) sts128(SM_BITS + tid * 16, 0, 0, 0, 0);
#pragma unroll
        for (int k = 0; k < 4; k++) {
            const unsigned pos = tid + k * (NCONS * 32), st = pos >> 3, j = pos & 7;
            dsc[k] = pin(pos | (((st % NX) * 8 + j) << 11) | ((((st % NR) * 8 + j) * (RSTR / 32)) << 21));
        }
        const char* const xi = pin64((const char*)(p.xch + cta * (NCTA * NCH) + tid));
        uint4 rc[3];
        rc[0].w = rc[1].w = 0;
        rc[2].w = h2 ? 0 : ep;
        rc[2].x = ~0u;
        nsync<8, NXT + 32>();
        TK(18, e0);
        {
            bool bad;
            int it = 0;
            do {
#pragma unroll
                for (int k = 0; k < 3; k++)
                    asm volatile("{.reg .pred q; .reg .b32 t; xor.b32 t, %3, %5; setp.gt.u32 q, t, 0xFFFF;\n @q ld.relaxed.gpu.global.v4.u32 {%0,%1,%2,%3}, [%4];}"
                                 : "+r"(rc[k].x), "+r"(rc[k].y), "+r"(rc[k].z), "+r"(rc[k].w) : "l"(xi + k * (NXT * 16)), "r"(ep) : "memory");
                bad = ((rc[0].w ^ ep) | (rc[1].w ^ ep) | (rc[2].w ^ ep)) > 0xFFFF;
            } while (__any_sync(~0u, bad) && ++it < 4096);
            if (bad || ((rc[0].w | rc[1].w | rc[2].w) & 1)) {
                rc[0].x = rc[1].x = rc[2].x = ~0u;
                sts32(totA + 4, CAP + 1);
            }
#ifdef DBG_PRO
            if (tid == 0) sts32(totA + 20, it * 2);
#endif
        }
        TK(2, e0);
        unsigned ord[3][3], ba[3][3], ve[3][3];
#pragma unroll
        for (int k = 0; k < 3; k++) {
            const unsigned rr[3] = {rc[k].x, rc[k].y, rc[k].z};
            if (rr[0] < DUM) {
#pragma unroll
                for (int j = 0; j < 3; j++) { ba[k][j] = pin((rr[j] >> (18 + BSH)) * 4); ord[k][j] = atoms_add(SM_BKT + ba[k][j], 4); }
            }
        }
        sts32(SM_CNT + warp * 4, __reduce_max_sync(~0u, max(rc[0].w, max(rc[1].w, rc[2].w))));
        narrive<9, NXT + 32>();
        TK(15, e0);
#pragma unroll
        for (int k = 0; k < 3; k++) {
            const unsigned rr[3] = {rc[k].x, rc[k].y, rc[k].z};
#pragma unroll
            for (int j = 0; j < 3; j++) ve[k][j] = pin((rr[j] & 0xFFFC07FF) + cc[k] * EPC);
        }
        cta_sync();
        TK(19, e0);
        total = __shfl_sync(~0u, lds32(totA + 8), 0);
        T0 = lds32(totA + 12);
#pragma unroll
        for (int k = 0; k < 3; k++) {
            if (rc[k].x < DUM) {
#pragma unroll
                for (int j = 0; j < 3; j++) ord[k][j] += lds32(SM_BKT + ba[k][j]);
#pragma unroll
                for (int j = 0; j < 3; j++)
                    asm volatile("{.reg .pred q; setp.lt.u32 q, %0, " STR(CAP) "*4;\n @q st.shared.u32 [%0+" STR(SM_EID) "], %1;}" ::"r"(ord[k][j]), "r"(ve[k][j]) : "memory");
            }
        }
        slow = total > CAP;
        if (!slow) {
            if (warp < NCONS) narrive<0, 512>();
#pragma unroll
            for (int k = 0; k < 3; k++) {
                const unsigned rr[3] = {rc[k].x, rc[k].y, rc[k].z};
                if (rr[0] < DUM) {
#pragma unroll
                    for (int j = 0; j < 3; j++)
                        asm volatile("{.reg .pred q; setp.lt.u32 q, %0, " STR(CAP) "*4;\n @q st.shared.u32 [%0+" STR(SM_SRC) "], %1;}" ::"r"(ord[k][j]), "r"(rr[j]) : "memory");
                }
            }
            if (warp == NCONS) narrive<11, NXT>();
        }
        nst = (total + 7) >> 3;
        const unsigned lim = (nst % NX) << 14;
#pragma unroll
        for (int k = 0; k < 4; k++) dsc[k] = pin(dsc[k] - lim + ((dsc[k] & 0x3C000) >= lim ? 0 : NX << 14));
        TK(20, e0);
#ifdef DBG_PRO
        if (tid == 0) { sts128(SM_NEXT + CAPP * 4, tk0, tk1, tk24, tk26); sts128(SM_NEXT + CAPP * 4 + 16, tk28, tk16, tk2, tk15); sts128(SM_NEXT + CAPP * 4 + 32, tk19, tk20, tk18, tstart); }
#endif
    }

    int wid = warp;
    if (slow) {
        asm volatile("fence.mbarrier_init.release.cluster;" ::: "memory");
        fence_async();
        cta_sync();
        if (tid < 4) { bar_expect(wbar + tid * 8, 16384); tma_2d(SB + tid * 16384, &tmw, wbar + tid * 8, tid * 64, 0); }
        slow_path(p);
    } else if (warp < NCONS) {
        nsync<11, NXT>();
        TK(3, tid);
        unsigned q[4], a[4];
        const bool k3 = warp * 32 + 3 * NCONS * 32 < total;
#pragma unroll
        for (int k = 0; k < 4; k++) if (k < 3 || k3) q[k] = lds32(SM_SRC + tid * 4 + k * (NCONS * 128));
#pragma unroll
        for (int k = 0; k < 4; k++) if (k < 3 || k3) {
            a[k] = ((q[k] >> 14) & 15) * (BW * 4) + warp * 4;
            asm volatile("red.shared.or.b32 [%0], %1;" ::"r"(SM_BITS + k * (NCONS * 4) + a[k]), "r"(1u << lane) : "memory");
        }
        __syncwarp();
#pragma unroll
        for (int k = 0; k < 4; k++) if (k < 3 || k3) a[k] = lds32(SM_BITS + k * (NCONS * 4) + a[k]);
#pragma unroll
        for (int k = 0; k < 4; k++) if (k < 3 || k3)
            sts32(SM_NEXT + k * (NCONS * 128) + ((warp * 32) | ((lane + 31 - __clz(__funnelshift_r(a[k], a[k], lane))) & 31)) * 4, dsc[k] | ((q[k] << 7) & 0x1C0000));
        asm volatile("bar.sync 5, %0;" ::"n"(NCONS * 32) : "memory");
        TK(21, tid);
        unsigned head;
        {
            const unsigned c = 31 - lane, m0 = lds32(SM_BITS + warp * (BW * 4) + c * 4), m1 = lds32(SM_BITS + warp * (BW * 4) + 128 + min(c, 12) * 4);
            const unsigned l0 = m0 ? c * 32 + 31 - __clz(m0) : CAPP - 1, l1 = m1 ? c * 32 + 1055 - __clz(m1) : CAPP - 1;
            const unsigned f0 = lds32(SM_NEXT + l0 * 4), f1 = lane ? lds32(SM_NEXT + l1 * 4) : 0x1C0000 | (warp << 21);
            const unsigned b0 = __ballot_sync(~0u, m0), b1 = __ballot_sync(~0u, m1) | 1, lt = (1u << lane) - 1;
            const unsigned h1 = __shfl_sync(~0u, f1, 31 - __clz(b1)), n1 = __shfl_sync(~0u, f1, 31 - __clz(b1 & lt));
            const unsigned h0 = __shfl_sync(~0u, f0, 31 - __clz(b0)), n0 = __shfl_sync(~0u, f0, 31 - __clz(b0 & lt));
            sts32(SM_NEXT + l0 * 4, b0 & lt ? n0 : h1);
            sts32(SM_NEXT + l1 * 4, n1);
            head = b0 ? h0 : h1;
            __syncwarp();
        }
        TK(22, tid);
#ifdef DBG_PRO
        if (tid == 0) sts128(SM_NEXT + CAPP * 4 + 48, tk3, tk21, tk22, 0);
#endif
        wid = consumer(head);
    } else if (warp == NCONS) {
        cta_sync();
        STAMPS(636 + 26, clk() | 1);
        const unsigned late = issuer(&tmx, p, nst, T0);
        wid = NCONS;
        if ((total & 7) && elect()) asm volatile("mbarrier.arrive.shared::cta.b64 _, [%0], %1;" ::"r"(SM_EMPTY + nst * 8 - 8), "r"(8 - (total & 7)) : "memory");
        STAMPS(11, clk() | 1); STAMPS(14, lds32(SM_MISC + 104)); STAMPS(12, tstart & ~1);
#pragma unroll 1
        for (int i = 0; i < 4; i++) {
            bwait(SM_EMPTY + (nst + i - NX) * 8);
            if (elect()) { bar_expect(wbar + i * 8, 16384); tma_2d(SB + i * 16384, &tmw, wbar + i * 8, i * 64, 0); }
        }
#ifdef DBG_TR
        for (int i = lane; i < nst; i += 32) g_trace[(cta * 180 + i) * 4 + 3] = lds32(SM_TR + i * 8) - T0;
#endif
#ifdef DBG_PRO
        if (lane < 15) { const unsigned ix[15] = {0, 1, 24, 26, 28, 16, 2, 15, 19, 20, 18, 31, 3, 21, 22}; unsigned j = 0;
#pragma unroll
            for (int q = 0; q < 15; q++) j = lane == q ? ix[q] : j;
            const unsigned v = lds32(SM_NEXT + CAPP * 4 + lane * 4); g_times[cta * 32 + j] = j == 31 ? v & ~1 : v | 1; }
        STAMPW(13, lds32(totA + 16)); STAMPW(17, lds32(totA + 20));
#endif
#ifdef DBG_H
        STAMPS(8, late & ~1);
#endif
        STAMPS(10, clk() | 1); STAMPS(7, T0 | 1);
    } else {
        const unsigned ewait = recorder(p, __shfl_sync(~0u, (tid >> 5) & 1, 0), nst, cg0, cg1);
        wid = NCONS + 1 + ((ewait >> 3) & 1);
#ifdef DBG_R
        if (wid == 15) STAMPW(12, ewait); else STAMPW(11, ewait);
#endif
    }

    wid = __shfl_sync(~0u, wid, 0);
    const int wg = wid >> 2, wq = wid & 3;
    int ln;
    asm volatile("mov.u32 %0, %%laneid;" : "=r"(ln));
    const bool lead = wq == 0 && ln == 0;
    unsigned af[16][4];
    const unsigned wt = SB + wg * 16384;
    const unsigned wa = wt + (((ln >> 4) * 8 + (ln & 7)) << 7) + (((2 * wq + ((ln >> 3) & 1)) ^ (ln & 7)) << 4);
    STAMPL(13);
    bwait(wbar + wg * 8);
#pragma unroll
    for (int k = 0; k < 8; k++) ldsm4t(af[k], wa + k * 2048);
    fence_async();
    cta_sync();
    STAMPL(5);
    if (lead) { bar_expect(wbar + 32 + wg * 8, 16384); tma_2d(wt, &tmw, wbar + 32 + wg * 8, wg * 64, 128); }
    const uint64_t desc0 = (uint64_t)(((SM_H) >> 4) & 0x3FFF) | (1ull << 16) | (64ull << 32) | (1ull << 62);
    float d[32];
    const int row0 = cta * (NPC * 4);
    wg_fence();
#pragma unroll
    for (int k = 0; k < 8; k++) wgmma_rs<64>(d, af[k], desc0 + (k >> 2) * (HPANEL >> 4) + (k & 3) * 2, k != 0);
    wg_commit();
    bwait(wbar + 32 + wg * 8);
#pragma unroll
    for (int k = 0; k < 8; k++) ldsm4t(af[8 + k], wa + k * 2048);
    wg_fence();
#pragma unroll
    for (int k = 8; k < 16; k++) wgmma_rs<64>(d, af[k], desc0 + (k >> 2) * (HPANEL >> 4) + (k & 3) * 2, 1);
    wg_commit();
    wg_wait0();
    out_chunk<64>(d, wt, &tmo, wg, row0, true, wa, lead);
#pragma unroll 1
    for (int c = 1; c < 4; c++) {
        wg_fence();
#pragma unroll
        for (int k = 0; k < 16; k++) wgmma_rs<64>(d, af[k], desc0 + c * 512 + (k >> 2) * (HPANEL >> 4) + (k & 3) * 2, k != 0);
        wg_commit();
        wg_wait0();
        out_chunk<64>(d, wt, &tmo, wg, row0 + c * 64, false, wa, lead);
    }
    wg_fence();
#pragma unroll
    for (int k = 0; k < 16; k++) wgmma_rs<48>(d, af[k], desc0 + 4 * 512 + (k >> 2) * (HPANEL >> 4) + (k & 3) * 2, k != 0);
    wg_commit();
    wg_wait0();
    out_chunk<48>(d, wt, &tmo, wg, row0 + 256, false, wa, lead);
    if (lead) asm volatile("cp.async.bulk.wait_group.read 0;" ::: "memory");
    STAMPL(6);
#ifdef DBG_TIMES
    if (wid == 8) STAMPS(4, clk() | 1);
    cta_sync();
    if (wid == 0 && ln >= 4 && ln < 21) g_times[cta * 32 + (ln == 12 ? 31 : ln)] = lds32(SM_BITS + ln * 4);
#endif
#ifdef DBG_GT
    { unsigned g; asm volatile("mov.u32 %0, %%globaltimer_lo;" : "=r"(g)); STAMPW(30, g & ~1); }
#endif
}

typedef CUresult (*EncFn)(CUtensorMap*, CUtensorMapDataType, cuuint32_t, void*, const cuuint64_t*, const cuuint64_t*, const cuuint32_t*,
                          const cuuint32_t*, CUtensorMapInterleave, CUtensorMapSwizzle, CUtensorMapL2promotion, CUtensorMapFloatOOBfill);

extern "C" void kernel_launch(void* const* d_in, const int* in_sizes, int n_in, void* d_out, int out_size) {
    static EncFn enc = nullptr;
    static int nsm = 0;
    static void* xch = nullptr;
    if (!enc) {
        void* fn = nullptr; cudaDriverEntryPointQueryResult qr;
        cudaGetDriverEntryPoint("cuTensorMapEncodeTiled", &fn, cudaEnableDefault, &qr);
        enc = (EncFn)fn;
        cudaGetSymbolAddress(&xch, g_xch);
        int dev = 0; cudaGetDevice(&dev);
        cudaDeviceGetAttribute(&nsm, cudaDevAttrMultiProcessorCount, dev);
        cudaFuncSetAttribute(mace_kernel, cudaFuncAttributeMaxDynamicSharedMemorySize, SM_TOTAL);
    }
    Params p;
    p.x = (const __nv_bfloat16*)d_in[0]; p.src = (const int*)d_in[1]; p.dst = (const int*)d_in[2];
    p.sh = (const __nv_bfloat16*)d_in[3]; p.ea = (const __nv_bfloat16*)d_in[4]; p.cg = (const __nv_bfloat16*)d_in[5];
    p.wr = (const __nv_bfloat16*)d_in[6]; p.wo = (const __nv_bfloat16*)d_in[7];
    p.N = in_sizes[0] / 1024; p.E = in_sizes[1];
    p.Ef = (nsm >= NCTA && p.N <= NCTA * NPC && p.E <= NCTA * EPC && p.N > 1 && (p.E & 3) == 0) ? p.E : 0;
    p.xch = (uint4*)xch;
    p.rate = (unsigned)((double)PACE * ((double)p.E / 160000.0) * 16384.0 / (double)p.N);
    p.zero = 0;
    CUtensorMap tmx, tmw, tmo;
    const cuuint32_t es[3] = {1, 1, 1};
    {
        cuuint64_t dims[3] = {64, (cuuint64_t)p.N * 4, 4}; cuuint64_t str[2] = {512, 128}; cuuint32_t box[3] = {64, 4, 4};
        enc(&tmx, CU_TENSOR_MAP_DATA_TYPE_BFLOAT16, 3, d_in[0], dims, str, box, es, CU_TENSOR_MAP_INTERLEAVE_NONE, CU_TENSOR_MAP_SWIZZLE_128B, CU_TENSOR_MAP_L2_PROMOTION_NONE, CU_TENSOR_MAP_FLOAT_OOB_FILL_NONE);
    }
    {
        cuuint64_t dims[2] = {256, 256}; cuuint64_t str[1] = {512}; cuuint32_t box[2] = {64, 128};
        enc(&tmw, CU_TENSOR_MAP_DATA_TYPE_BFLOAT16, 2, d_in[7], dims, str, box, es, CU_TENSOR_MAP_INTERLEAVE_NONE, CU_TENSOR_MAP_SWIZZLE_128B, CU_TENSOR_MAP_L2_PROMOTION_NONE, CU_TENSOR_MAP_FLOAT_OOB_FILL_NONE);
    }
    {
        cuuint64_t dims[2] = {256, (cuuint64_t)p.N * 4}; cuuint64_t str[1] = {512}; cuuint32_t box[2] = {64, 16};
        enc(&tmo, CU_TENSOR_MAP_DATA_TYPE_BFLOAT16, 2, d_out, dims, str, box, es, CU_TENSOR_MAP_INTERLEAVE_NONE, CU_TENSOR_MAP_SWIZZLE_128B, CU_TENSOR_MAP_L2_PROMOTION_NONE, CU_TENSOR_MAP_FLOAT_OOB_FILL_NONE);
    }
    const int grid = p.Ef ? NCTA : (p.N + NPC - 1) / NPC;
    mace_kernel<<<grid, 512, SM_TOTAL>>>(p, tmx, tmw, tmo);
}
```

```cpp
#include <cuda_runtime.h>
#include <cuda_bf16.h>
#include <cuda.h>
#include <stdint.h>

#ifndef NX
#define NX 10
#endif
#ifndef NR
#define NR 9
#endif
#ifndef PACE
#define PACE 49500
#endif
#ifndef T0DELTA
#define T0DELTA 4900
#endif
#ifndef BSH
#define BSH 5
#endif
#ifndef POLLT
#define POLLT 3700
#endif
#ifndef PFT
#define PFT 5500
#endif
#ifndef PF1
#define PF1 0
#endif
#ifndef PFLEAD
#define PFLEAD 8
#endif
#ifndef RSPL
#define RSPL 10
#endif
#ifndef RLDG
#define RLDG "ld.global.nc"
#endif
#ifndef DISP
#define DISP 1
#endif
#ifndef XST
#define XST "st.relaxed.gpu.global.v4.u32"
#endif
#define NCTA 132
#define NPC 76
#define EPC 1216
#define NCH 10
#define CAP 1376
#define CAPP 1440
#define NCONS 13
#define RSTR 608
#define NBW ((((NCTA * NPC) >> BSH) + 128) / 128)

#define SB 1024
#define SM_X SB
#define SM_R (SM_X + NX * 16384)
#define SM_EID (SM_R + NR * 8 * RSTR)
#define SM_NEXT (SM_EID + 6144)
#define SM_H (SB + 65536)
#define HPANEL 38912
#define SM_FULL (SM_H + 4 * HPANEL)
#define SM_EMPTY (SM_FULL + CAPP + 128)
#define SM_SRC (SM_EMPTY + CAPP)
#define SM_BITS (SM_SRC + 1392 * 4)
#define SM_MISC (SM_BITS + 2544)
#define SM_TOTAL (SM_MISC + 128 - SB)
#define NXT 448
#define SM_STAGE SM_R
#define SM_CNT (SM_R + NXT * 48)
#define SM_WR (SM_CNT + 640)
#define SM_BKT (SM_WR + 16 * 528)
static_assert(SM_BKT + NBW * 512 + 128 <= SM_EID, "smem");
#define DUM ((unsigned)(NBW * 128) << (18 + BSH))
#define BW 45
static_assert(SM_NEXT + CAPP * 4 <= SM_FULL && SM_TOTAL <= 232448, "smem");
#define STR_(x) #x
#define STR(x) STR_(x)

__device__ uint4 g_xch[NCTA * NCTA * NCH + 8];
#ifdef DBG_TIMES
extern "C" { __device__ unsigned g_times[NCTA * 32]; }
#define STAMPV(m, i, v) asm volatile("{.reg .pred q; .reg .b32 t; .reg .b64 a, b; mov.u32 t, %%tid.x; and.b32 t, t, %0; setp.eq.u32 q, t, 0; mov.u32 t, %%ctaid.x; mov.u64 b, g_times; mad.wide.u32 a, t, 128, b; @q st.global.u32 [a+%1], %2;}" ::"n"(m), "n"((i) * 4), "r"(v) : "memory")
#define STAMP(i) STAMPV(1023, i, clk() | 0x1)
#define STAMPS(i, v) sts32(SM_BITS + (i) * 4, v)
#define STAMPL(i) if (wid == 0) STAMPS(i, clk() | 0x1)
#define STAMPW(i, v) asm volatile("{.reg .b32 t; .reg .b64 a, b; mov.u32 t, %%ctaid.x; mov.u64 b, g_times; mad.wide.u32 a, t, 128, b; st.global.u32 [a+%0], %1;}" ::"n"((i) * 4), "r"(v) : "memory")
#define TK(i, dep) unsigned tk##i; asm volatile("{.reg .b32 t; and.b32 t, %1, %2; mov.u32 %0, %%clock; add.u32 %0, %0, t;}" : "=r"(tk##i) : "r"(dep), "r"(p.zero) : "memory")
#define TKO(i) STAMPV(1023, i, tk##i | 1)
#ifndef DBG_PRO
#undef TK
#define TK(i, dep)
#endif
#else
#define STAMP(i)
#define STAMPL(i)
#define STAMPS(i, v)
#define STAMPV(m, i, v)
#define STAMPW(i, v)
#define TK(i, dep)
#define TKO(i)
#endif

struct Params {
    const int* src; const int* dst; uint4* xch; const __nv_bfloat16* wr;
    int Ef, N;
    const __nv_bfloat16* cg; const __nv_bfloat16* x; const __nv_bfloat16* sh; const __nv_bfloat16* ea; const __nv_bfloat16* wo;
    int E; unsigned rate, zero;
};

__device__ __forceinline__ unsigned clk() { unsigned c; asm volatile("mov.u32 %0, %%clock;" : "=r"(c)); return c; }
__device__ __forceinline__ bool elect() { unsigned p; asm volatile("{.reg .pred P; elect.sync _|P, 0xffffffff; selp.u32 %0,1,0,P;}" : "=r"(p)); return p; }
__device__ __forceinline__ bool try_wait(unsigned a) { unsigned ok; asm volatile("{.reg .pred p; mbarrier.try_wait.parity.shared::cta.b64 p,[%1],0; selp.u32 %0,1,0,p;}" : "=r"(ok) : "r"(a) : "memory"); return ok; }
__device__ __forceinline__ void bwait(unsigned a) { if (!try_wait(a)) { for (int i = 0; i < (1 << 18) && !try_wait(a); i++); } }
__device__ __forceinline__ unsigned pin(unsigned x) { unsigned y; asm volatile("mov.u32 %0, %1;" : "=r"(y) : "r"(x)); return y; }
__device__ __forceinline__ const char* pin64(const char* x) { const char* y; asm volatile("mov.u64 %0, %1;" : "=l"(y) : "l"(x)); return y; }
__device__ __forceinline__ void split(unsigned x, unsigned c) { asm volatile("{.reg .pred p; setp.eq.u32 p, %0, %1; @p exit;}" ::"r"(x), "r"(c) : "memory"); }
__device__ __forceinline__ void bar_init(unsigned a, unsigned c) { asm volatile("mbarrier.init.shared::cta.b64 [%0], %1;" ::"r"(a), "r"(c) : "memory"); }
__device__ __forceinline__ void bar_expect(unsigned a, unsigned bytes) { asm volatile("mbarrier.arrive.expect_tx.shared::cta.b64 _, [%0], %1;" ::"r"(a), "r"(bytes) : "memory"); }
__device__ __forceinline__ void bar_complete(unsigned a, unsigned bytes) { asm volatile("mbarrier.complete_tx.relaxed.cta.shared::cta.b64 [%0], %1;" ::"r"(a), "r"(bytes) : "memory"); }
__device__ __forceinline__ void fence_async() { asm volatile("fence.proxy.async.shared::cta;" ::: "memory"); }
template <int ID, int N> __device__ __forceinline__ void nsync() { asm volatile("bar.sync %0, %1;" ::"n"(ID), "n"(N) : "memory"); }
template <int ID, int N> __device__ __forceinline__ void narrive() { asm volatile("bar.arrive %0, %1;" ::"n"(ID), "n"(N) : "memory"); }
__device__ __forceinline__ void cta_sync() { asm volatile("bar.sync 0, 512;" ::: "memory"); }
__device__ __forceinline__ unsigned lds32(unsigned a) { unsigned v; asm volatile("ld.shared.u32 %0,[%1];" : "=r"(v) : "r"(a) : "memory"); return v; }
__device__ __forceinline__ unsigned lds16(unsigned a) { unsigned v; asm volatile("ld.shared.u16 %0,[%1];" : "=r"(v) : "r"(a) : "memory"); return v; }
__device__ __forceinline__ uint4 lds128(unsigned a) { uint4 v; asm volatile("ld.shared.v4.u32 {%0,%1,%2,%3},[%4];" : "=r"(v.x), "=r"(v.y), "=r"(v.z), "=r"(v.w) : "r"(a) : "memory"); return v; }
__device__ __forceinline__ void sts32(unsigned a, unsigned v) { asm volatile("st.shared.u32 [%0],%1;" ::"r"(a), "r"(v) : "memory"); }
__device__ __forceinline__ void sts16(unsigned a, unsigned v) { asm volatile("st.shared.u16 [%0],%1;" ::"r"(a), "r"(v) : "memory"); }
__device__ __forceinline__ void sts64(unsigned a, unsigned x, unsigned y) { asm volatile("st.shared.v2.u32 [%0],{%1,%2};" ::"r"(a), "r"(x), "r"(y) : "memory"); }
__device__ __forceinline__ void sts128(unsigned a, unsigned x, unsigned y, unsigned z, unsigned w) { asm volatile("st.shared.v4.u32 [%0],{%1,%2,%3,%4};" ::"r"(a), "r"(x), "r"(y), "r"(z), "r"(w) : "memory"); }
__device__ __forceinline__ unsigned atoms_add(unsigned a, unsigned v) { unsigned o; asm volatile("atom.shared.add.u32 %0,[%1],%2;" : "=r"(o) : "r"(a), "r"(v) : "memory"); return o; }
__device__ __forceinline__ void ldsm4t(unsigned* r, unsigned a) { asm volatile("ldmatrix.sync.aligned.m8n8.x4.trans.shared.b16 {%0,%1,%2,%3},[%4];" : "=r"(r[0]), "=r"(r[1]), "=r"(r[2]), "=r"(r[3]) : "r"(a) : "memory"); }
__device__ __forceinline__ void stsm4t(unsigned a, unsigned r0, unsigned r1, unsigned r2, unsigned r3) { asm volatile("stmatrix.sync.aligned.m8n8.x4.trans.shared.b16 [%0],{%1,%2,%3,%4};" ::"r"(a), "r"(r0), "r"(r1), "r"(r2), "r"(r3) : "memory"); }
__device__ __forceinline__ unsigned pack2(float lo, float hi) { unsigned p; asm("cvt.rn.bf16x2.f32 %0,%1,%2;" : "=r"(p) : "f"(hi), "f"(lo)); return p; }
__device__ __forceinline__ void mma1688(float* d, unsigned a0, unsigned a1, unsigned b0) {
    asm("mma.sync.aligned.m16n8k8.row.col.f32.bf16.bf16.f32 {%0,%1,%2,%3},{%4,%5},{%6},{%7,%7,%7,%7};"
        : "=f"(d[0]), "=f"(d[1]), "=f"(d[2]), "=f"(d[3]) : "r"(a0), "r"(a1), "r"(b0), "f"(0.f));
}
__device__ __forceinline__ void mma16816(float* d, const unsigned* a, unsigned b0, unsigned b1) {
    asm volatile("mma.sync.aligned.m16n8k16.row.col.f32.bf16.bf16.f32 {%0,%1,%2,%3},{%4,%5,%6,%7},{%8,%9},{%10,%10,%10,%10};"
        : "=f"(d[0]), "=f"(d[1]), "=f"(d[2]), "=f"(d[3]) : "r"(a[0]), "r"(a[1]), "r"(a[2]), "r"(a[3]), "r"(b0), "r"(b1), "f"(0.f));
}
__device__ __forceinline__ void tma_x(unsigned da, const void* tm, unsigned ba, int c1) {
    asm volatile("cp.async.bulk.tensor.3d.shared::cluster.global.mbarrier::complete_tx::bytes [%0], [%1, {%3,%4,%3}], [%2];" ::"r"(da), "l"(tm), "r"(ba), "r"(0), "r"(c1) : "memory");
}
__device__ __forceinline__ void tma_2d(unsigned da, const CUtensorMap* tm, unsigned ba, int c0, int c1) {
    asm volatile("cp.async.bulk.tensor.2d.shared::cluster.global.mbarrier::complete_tx::bytes [%0], [%1, {%3,%4}], [%2];" ::"r"(da), "l"(tm), "r"(ba), "r"(c0), "r"(c1) : "memory");
}
__device__ __forceinline__ void tma_st(const CUtensorMap* tm, unsigned sa, int c0, int c1) {
    asm volatile("cp.async.bulk.tensor.2d.global.shared::cta.bulk_group [%0, {%2,%3}], [%1];" ::"l"(tm), "r"(sa), "r"(c0), "r"(c1) : "memory");
}
__device__ __forceinline__ void pf_l2(const void* p, unsigned bytes) { asm volatile("cp.async.bulk.prefetch.L2.global [%0], %1;" ::"l"(p), "r"(bytes) : "memory"); }

#define WG_REGS24(d) "+f"(d[0]), "+f"(d[1]), "+f"(d[2]), "+f"(d[3]), "+f"(d[4]), "+f"(d[5]), "+f"(d[6]), "+f"(d[7]), \
    "+f"(d[8]), "+f"(d[9]), "+f"(d[10]), "+f"(d[11]), "+f"(d[12]), "+f"(d[13]), "+f"(d[14]), "+f"(d[15]), \
    "+f"(d[16]), "+f"(d[17]), "+f"(d[18]), "+f"(d[19]), "+f"(d[20]), "+f"(d[21]), "+f"(d[22]), "+f"(d[23])
template <int NN> __device__ __forceinline__ void wgmma_rs(float* d, const unsigned* a, uint64_t desc, int scale_d);
template <> __device__ __forceinline__ void wgmma_rs<48>(float* d, const unsigned* a, uint64_t desc, int scale_d) {
    asm volatile("{.reg .pred p; setp.ne.b32 p, %29, 0;\n"
        "wgmma.mma_async.sync.aligned.m64n48k16.f32.bf16.bf16 {%0,%1,%2,%3,%4,%5,%6,%7,%8,%9,%10,%11,%12,%13,%14,%15,%16,%17,%18,%19,"
        "%20,%21,%22,%23}, {%24,%25,%26,%27}, %28, p, 1, 1, 0;}"
        : WG_REGS24(d)
        : "r"(a[0]), "r"(a[1]), "r"(a[2]), "r"(a[3]), "l"(desc), "r"(scale_d));
}
template <> __device__ __forceinline__ void wgmma_rs<64>(float* d, const unsigned* a, uint64_t desc, int scale_d) {
    asm volatile("{.reg .pred p; setp.ne.b32 p, %37, 0;\n"
        "wgmma.mma_async.sync.aligned.m64n64k16.f32.bf16.bf16 {%0,%1,%2,%3,%4,%5,%6,%7,%8,%9,%10,%11,%12,%13,%14,%15,%16,%17,%18,%19,"
        "%20,%21,%22,%23,%24,%25,%26,%27,%28,%29,%30,%31}, {%32,%33,%34,%35}, %36, p, 1, 1, 0;}"
        : WG_REGS24(d), "+f"(d[24]), "+f"(d[25]), "+f"(d[26]), "+f"(d[27]), "+f"(d[28]), "+f"(d[29]), "+f"(d[30]), "+f"(d[31])
        : "r"(a[0]), "r"(a[1]), "r"(a[2]), "r"(a[3]), "l"(desc), "r"(scale_d));
}
__device__ __forceinline__ void wg_fence() { asm volatile("wgmma.fence.sync.aligned;" ::: "memory"); }
__device__ __forceinline__ void wg_commit() { asm volatile("wgmma.commit_group.sync.aligned;" ::: "memory"); }
__device__ __forceinline__ void wg_wait0() { asm volatile("wgmma.wait_group.sync.aligned 0;" ::: "memory"); }

#define PF(D, RW, K, J0, J1) \
    "cvt.rn.bf16x2.f32 t0, " #D "1, " #D "0;\n cvt.rn.bf16x2.f32 t1, " #D "3, " #D "2;\n" \
    "mov.b32 {lo, hi}, " #RW ";\n mov.b32 u0, {lo, lo};\n mov.b32 u1, {hi, hi};\n" \
    "fma.rn.bf16x2 a" #K "_" #J0 ", t0, u0, a" #K "_" #J0 ";\n fma.rn.bf16x2 a" #K "_" #J1 ", t1, u1, a" #K "_" #J1 ";\n"
#define MMA(D, A0, A1) "mma.sync.aligned.m16n8k8.row.col.f32.bf16.bf16.f32 {" #D "0," #D "1," #D "2," #D "3}, {" #A0 "," #A1 "}, {bf}, {fz,fz,fz,fz};\n"
#define LDX(X, OFF) "ldmatrix.sync.aligned.m8n8.x4.trans.shared.b16 {" #X "0," #X "1," #X "2," #X "3}, [xa+" STR(SM_X) "+" #OFF "];\n"
#define DECODE \
    "lop3.b32 xa, dn, 0x3F800, %1, 0xEA;\n" \
    "shr.u32 t2, dn, 21;\n mad.lo.u32 ra, t2, 32, %2;\n mad.lo.u32 ca, t2, 32, %3;\n" \
    "and.b32 t3, dn, 0x7FF;\n shl.b32 t3, t3, 2;\n" SETD
#define LOADS \
    LDX(x, 0) "@act ld.shared.u32 bf, [ca+" STR(SM_R) "];\n" LDX(y, 512) LDR(r, 0) \
    "ld.shared.u32 dn, [t3+" STR(SM_NEXT) "];\n"
#if DISP == 0
#define SETD "bfe.u32 ix, dn, 18, 3;\n"
#define DISPATCH "brx.idx.uni ix, TS;\n"
#define T23
#define T45
#else
#define SETD "and.b32 ix, dn, 0x40000;\n setp.ne.u32 q0, ix, 0;\n and.b32 ix, dn, 0x80000;\n setp.ne.u32 q1, ix, 0;\n and.b32 ix, dn, 0x100000;\n setp.ne.u32 q2, ix, 0;\n"
#define DISPATCH "@q2 bra.uni T45;\n @q1 bra.uni T23;\n @q0 bra.uni B1;\n bra.uni B0;\n"
#define T23 "T23:\n @q0 bra.uni B3;\n"
#define T45 "T45:\n @q1 bra.uni FIN;\n @q0 bra.uni B5;\n"
#endif
#define LDR(R, OFF) "ld.shared.v4.u32 {" #R "0," #R "1," #R "2," #R "3}, [ra+" STR(SM_R) "+" #OFF "];\n"
#ifdef JG
#define JIG "and.b32 t0, t0, 0xFFFF;\n"
#else
#define JIG
#endif
#define BODY(K) "B" #K ":\n" \
    MMA(d, x0, x1) MMA(e, x2, x3) LDX(x, 1024) "and.b32 bn, dn, 0x7F8;\n" \
    "mbarrier.test_wait.parity.shared::cta.b64 p, [bn+" STR(SM_FULL) "], 0;\n" \
    PF(d, r0, K, 0, 1) MMA(d, y0, y1) PF(e, r1, K, 2, 3) MMA(e, y2, y3) LDX(y, 1536) LDR(s, 128) \
    PF(d, r2, K, 4, 5) MMA(d, x0, x1) PF(e, r3, K, 6, 7) MMA(e, x2, x3) \
    PF(d, s0, K, 8, 9) MMA(d, y0, y1) \
    "@l0 mbarrier.arrive.shared::cta.b64 _, [bc+" STR(SM_EMPTY) "];\n" \
    PF(e, s1, K, 10, 11) MMA(e, y2, y3) \
    "mov.u32 bc, bn;\n" DECODE \
    "@!p bra.uni W" #K ";\n" \
    "R" #K ":\n" LOADS \
    PF(d, s2, K, 12, 13) PF(e, s3, K, 14, 15) DISPATCH
#ifdef DBG_TR
#define SM_TR (SM_NEXT + CAPP * 4)
#define TRC "mov.u32 t1, %%clock;\n st.shared.u32 [bc+" STR(SM_TR) "], t1;\n"
extern "C" { __device__ unsigned g_trace[NCTA * 4 * 180]; }
#else
#define TRC
#endif
#define WAIT(K) "W" #K ":\n mov.u32 t0, 0;\n" \
    "V" #K ":\n mbarrier.try_wait.parity.shared::cta.b64 p, [bc+" STR(SM_FULL) "], 0;\n" TRC "@p bra.uni R" #K ";\n" \
    "add.u32 t0, t0, 1;\n setp.lt.u32 p, t0, 400000;\n @p bra.uni V" #K ";\n bra.uni R" #K ";\n"
#define Z4(K, A, B, C, D) "mov.u32 a" #K "_" #A ", 0; mov.u32 a" #K "_" #B ", 0; mov.u32 a" #K "_" #C ", 0; mov.u32 a" #K "_" #D ", 0;\n"
#define ZACC(K) Z4(K, 0, 1, 2, 3) Z4(K, 4, 5, 6, 7) Z4(K, 8, 9, 10, 11) Z4(K, 12, 13, 14, 15)
#define ST4(K, A, B, C, D, R, P) "stmatrix.sync.aligned.m8n8.x4.trans.shared.b16 [" #R "+" STR(SM_H) "+" #K "*512+" #P "*" STR(HPANEL) "], {a" #K "_" #A ",a" #K "_" #B ",a" #K "_" #C ",a" #K "_" #D "};\n"
#define STP(P, A, B, C, D, R0, R1) ST4(0, A, B, C, D, R0, P) ST4(1, A, B, C, D, R1, P) ST4(2, A, B, C, D, R0, P) ST4(3, A, B, C, D, R1, P) \
    "@q0 bra.uni E" #P ";\n" ST4(4, A, B, C, D, R0, P) ST4(5, A, B, C, D, R1, P) "E" #P ":\n"
#define FS(P) "add.u32 t2, bn, " STR(SM_H) "-" STR(SM_X) "+" #P "*" STR(HPANEL) ";\n shr.u32 t2, t2, 14;\n mad.lo.u32 t2, t2, 8, bc;\n"
#define FW(ID, PRE, A) "@q1 bra.uni G" #ID ";\n" PRE "mov.u32 t3, 0;\n" \
    "F" #ID ":\n mbarrier.try_wait.parity.shared::cta.b64 p, [" #A "+" STR(SM_EMPTY) "-8*" STR(NX) "], 0;\n vote.sync.all.pred p, p, -1;\n" \
    "add.u32 t3, t3, 1;\n setp.lt.and.u32 p, t3, 400000, !p;\n @p bra.uni F" #ID ";\n G" #ID ":\n"
__device__ __forceinline__ unsigned consumer(unsigned head) {
    const int lane = threadIdx.x & 31, g = lane >> 2, t = lane & 3;
    const unsigned xl = (lane & 3) * 128 + ((((lane >> 3) + (lane & 4)) ^ (lane & 3)) << 4);
    const unsigned rl = (t >> 1) * 320 + g * 16;
    const unsigned cl = (t >> 1) == (g >> 2) ? 256 + (2 * (g & 3) + (t & 1)) * 4 : 0;
    asm volatile("{\n"
        ".reg .b32 a0_<16>, a1_<16>, a2_<16>, a3_<16>, a4_<16>, a5_<16>;\n"
        ".reg .b32 x<4>, y<4>, r<4>, s<4>, t<4>, u<2>, bf, xa, ra, ca, bn, bc, dn, ix;\n"
        ".reg .f32 d<4>, e<4>, fz;\n .reg .b16 lo, hi;\n .reg .pred p, q<3>, act, l0;\n"
#if DISP == 0
        "TS: .branchtargets B0, B1, B2, B3, B4, B5, FIN, FIN;\n"
#endif
        "mov.f32 fz, 0f00000000;\n mov.u32 bf, 0;\n setp.ne.u32 act, %3, 0;\n setp.eq.u32 l0, %1, 0;\n mov.u32 dn, %0;\n"
        ZACC(0) ZACC(1) ZACC(2) ZACC(3) ZACC(4) ZACC(5)
        "and.b32 bc, dn, 0x7F8;\n"
        DECODE "and.b32 t0, dn, 0x1C0000;\n setp.eq.u32 p, t0, 0x1C0000;\n @p bra.uni FIN;\n"
        WAIT(6)
        "R6:\n" LOADS DISPATCH
        BODY(0) BODY(1) T23 BODY(2) BODY(3) T45 BODY(4) BODY(5)
        WAIT(0) WAIT(1) WAIT(2) WAIT(3) WAIT(4) WAIT(5)
        "FIN:\n mov.u32 bc, " STR(SM_MISC) ";\n ld.shared.u32 bc, [bc+88];\n add.u32 bc, bc, 7;\n and.b32 bc, bc, -8;\n"
        "mov.u32 t2, %%laneid;\n min.u32 ca, t2, " STR(NX) "-1;\n mad.lo.u32 ca, ca, 8, bc;\n"
        "mbarrier.test_wait.parity.shared::cta.b64 p, [ca+" STR(SM_EMPTY) "-8*" STR(NX) "], 0;\n vote.sync.all.pred q1, p, -1;\n"
        "sub.u32 t0, ra, %2;\n" JIG "shr.u32 %0, t0, 5;\n mul.lo.u32 bn, t0, 96;\n"
        "add.u32 t0, bn, %1;\n xor.b32 t1, t0, 64;\n setp.eq.u32 q0, %0, 12;\n vote.sync.all.pred q0, q0, -1;\n and.b32 t2, t2, 1;\n mad.lo.u32 bn, t2, 3071, bn;\n"
        FW(0, FS(0), t2) STP(0, 0, 1, 2, 3, t0, t1) FW(1, FS(1), t2) STP(1, 4, 5, 6, 7, t1, t0) FW(2, , ca)
#ifdef DBG_TIMES
        "mov.u32 t2, %%clock;\n or.b32 t2, t2, 1;\n mov.u32 t3, " STR(SM_BITS) ";\n st.shared.u32 [t3+36], t2;\n"
#endif
        STP(2, 8, 9, 10, 11, t0, t1) STP(3, 12, 13, 14, 15, t1, t0)
        "}\n" : "+r"(head) : "r"(xl), "r"(rl), "r"(cl) : "memory");
    return head;
}

#define RMMA(D, Q, B0, B1) "mma.sync.aligned.m16n8k16.row.col.f32.bf16.bf16.f32 {" #D "0," #D "1," #D "2," #D "3}, {w" #Q "_0,w" #Q "_1,w" #Q "_2,w" #Q "_3}, {" #B0 "," #B1 "}, {fz,fz,fz,fz};\n"
#define RPK(I, D) "cvt.rn.bf16x2.f32 u" #I ", " #D "2, " #D "0;\n cvt.rn.bf16x2.f32 v" #I ", " #D "3, " #D "1;\n"
#define RG(Q0, Q1, Q2, Q3, B0, B1, A, OFF) \
    RMMA(da, Q0, B0, B1) RMMA(db, Q1, B0, B1) RMMA(dc, Q2, B0, B1) RMMA(dd, Q3, B0, B1) \
    RPK(0, da) RPK(1, db) RPK(2, dc) RPK(3, dd) \
    "st.shared.v4.u32 [" #A "+" #OFF "], {u0,u1,u2,u3};\n st.shared.v4.u32 [" #A "+" #OFF "+4*" STR(RSTR) "], {v0,v1,v2,v3};\n"
#define RSPLIT(M) "setp.eq.u32 pk, ro, " #M ";\n @pk exit;\n"
#if RSPL & 2
#define RS1 RSPLIT(1)
#else
#define RS1
#endif
#if RSPL & 4
#define RS2 RSPLIT(2)
#else
#define RS2
#endif
#if RSPL & 8
#define RS3 RSPLIT(3)
#else
#define RS3
#endif
#ifdef NOLOAD
#define RTX "0"
#else
#define RTX "16384"
#endif
#ifdef DBG_R
#define RW0 "mov.u32 tw, %%clock;\n"
#define RW1 "mov.u32 t0, %%clock;\n sub.u32 t0, t0, tw;\n add.u32 %0, %0, t0;\n"
#else
#define RW0
#define RW1
#endif
#ifdef XREC
#define RG2(B0, B1)
#else
#define RG2(B0, B1) RG(8, 9, 10, 11, B0, B1, a0, 128) RS3 RG(12, 13, 14, 15, B0, B1, a0, 448)
#endif
#define RSTAGE(ID, B0, B1, SEL, PRE, MID) \
    "@!pw bra.uni RW" #ID ";\n RR" #ID ":\n" PRE \
    "mbarrier.test_wait.parity.shared::cta.b64 pw, [sb+" STR(SM_EMPTY) "+16-8*" STR(NR) "], 0;\n" \
    "add.u32 a0, ro, %2;\n add.u32 a2, ro, %4;\n" \
    RG(0, 1, 2, 3, B0, B1, a0, 0) RS1 RG(4, 5, 6, 7, B0, B1, a0, 320) RS2 MID \
    "selp.b32 t0, " SEL ", pe;\n" \
    "mma.sync.aligned.m16n8k8.row.col.f32.bf16.bf16.f32 {da0,da1,da2,da3}, {%5,%6}, {t0}, {fz,fz,fz,fz};\n" RPK(0, da) \
    "st.shared.u32 [a2], u0;\n st.shared.u32 [a2+4*" STR(RSTR) "], v0;\n" \
    RG2(B0, B1) \
    "bar.warp.sync 0xffffffff;\n elect.sync _|l0, 0xffffffff;\n" \
    "@l0 mbarrier.arrive.expect_tx.shared::cta.b64 _, [sb+" STR(SM_FULL) "], " RTX ";\n" \
    "add.u32 sb, sb, 16;\n add.u32 ro, ro, 16*" STR(RSTR) ";\n setp.ge.u32 pk, ro, " STR(SM_EID) ";\n @pk sub.u32 ro, ro, 8*" STR(NR) "*" STR(RSTR) ";\n" \
    "setp.ge.u32 pk, sb, %9;\n @pk bra.uni REND;\n"
#define RWAIT(ID) "RW" #ID ":\n" RW0 "mov.u32 t1, 0;\n" \
    "RV" #ID ":\n mbarrier.try_wait.parity.shared::cta.b64 pk, [sb+" STR(SM_EMPTY) "-8*" STR(NR) "], 0;\n" \
    "add.u32 t1, t1, 1;\n setp.lt.and.u32 pk, t1, 400000, !pk;\n @pk bra.uni RV" #ID ";\n" RW1 "bra.uni RR" #ID ";\n"
#define RLD1(S, I, J, E) "shl.b32 " #E ", " #E ", 2;\n lop3.b32 " #E ", " #E ", 0xFFFFC, tt, 0xEA;\n mad.wide.u32 ad, " #E ", 8, %10;\n " RLDG ".v2.u32 {" #S #I "," #S #J "}, [ad];\n"
#define RLD2(S, I, E, F) "selp.b32 t1, " #E ", " #F ", pe;\n and.b32 t1, t1, -2;\n mad.wide.u32 ad, t1, 2, %11;\n " RLDG ".u32 " #S #I ", [ad];\n"
#define RLOAD(S, DEP) "lop3.b32 tt, " #DEP ", %12, %7, 0xEA;\n" \
    RLD1(S, 0, 1, e0) RLD1(S, 2, 3, e1) RLD2(S, 8, e0, e1) RLD1(S, 4, 5, e2) RLD1(S, 6, 7, e3) RLD2(S, 9, e2, e3)
#define REID1(I) "ld.shared.u32 e" #I ", [ea+" STR(SM_EID) "+64*" #I "];\n"
#define REID REID1(0) REID1(1) REID1(2) REID1(3) "add.u32 ea, ea, 256;\n"
#define RPF "mad.wide.u32 ad, pf, 4096, %14;\n add.u32 pf, pf, 2*" STR(NCTA) ";\n setp.lt.u32 pk, pf, %3;\n selp.b32 pf, pf, %3, pk;\n" \
    "elect.sync _|l0, 0xffffffff;\n @l0 cp.async.bulk.prefetch.L2.global [ad], 4096;\n"
#define RLDW(Q) "ldmatrix.sync.aligned.m8n8.x4.trans.shared.b16 {w" #Q "_0,w" #Q "_1,w" #Q "_2,w" #Q "_3}, [%1+2*(64*(2*(" #Q ">>3)+((" #Q "&3)>>1))+8*((2*(" #Q "&1)+(" #Q "&4))^(2*(" #Q "&2))))];\n"
__device__ __forceinline__ unsigned recorder(const Params& p, int hw, int nst, unsigned cg0, unsigned cg1) {
    const int lane = threadIdx.x & 31, g = lane >> 2, t = lane & 3, mi = lane >> 3, r = lane & 7;
    const unsigned wa = SM_WR + (4 * (r >> 1) + (r & 1) + 2 * (mi >> 1)) * 528 + (mi & 1) * 16;
    unsigned ewait = 0;
    asm volatile("{\n"
        ".reg .b32 w0_<4>, w1_<4>, w2_<4>, w3_<4>, w4_<4>, w5_<4>, w6_<4>, w7_<4>, w8_<4>, w9_<4>, w10_<4>, w11_<4>, w12_<4>, w13_<4>, w14_<4>, w15_<4>;\n"
        ".reg .b32 x<10>, y<10>, e<4>, u<4>, v<4>, a<3>, t<2>, tt, tw, ea, sb, ro, pf;\n .reg .b64 ad;\n"
        ".reg .f32 da<4>, db<4>, dc<4>, dd<4>, fz;\n .reg .pred pw, pk, pe, l0;\n"
        RLDW(0) RLDW(1) RLDW(2) RLDW(3) RLDW(4) RLDW(5) RLDW(6) RLDW(7) RLDW(8) RLDW(9) RLDW(10) RLDW(11) RLDW(12) RLDW(13) RLDW(14) RLDW(15)
        "mov.f32 fz, 0f00000000;\n and.b32 t0, %7, 1;\n setp.eq.u32 pe, t0, 0;\n"
        "mov.u32 pf, %15;\n mad.lo.u32 ea, %13, 32, %8;\n shl.b32 sb, %13, 3;\n mad.lo.u32 ro, %13, 8*" STR(RSTR) ", " STR(SM_R) ";\n"
        "bar.sync 0, 512;\n"
        "setp.lt.u32 pw, sb, %9;\n @!pw bra.uni REND;\n"
        REID RLOAD(x, %12) REID
        "RTOP:\n"
        RSTAGE(0, x0, x1, "x8, 0", RLOAD(y, x0), ) RSTAGE(1, x2, x3, "0, x8", , ) RSTAGE(2, x4, x5, "x9, 0", , RPF) RSTAGE(3, x6, x7, "0, x9", , REID)
        RSTAGE(4, y0, y1, "y8, 0", RLOAD(x, y0), ) RSTAGE(5, y2, y3, "0, y8", , ) RSTAGE(6, y4, y5, "y9, 0", , RPF) RSTAGE(7, y6, y7, "0, y9", , REID)
        "bra.uni RTOP;\n"
        RWAIT(0) RWAIT(1) RWAIT(2) RWAIT(3) RWAIT(4) RWAIT(5) RWAIT(6) RWAIT(7)
        "REND:\n and.b32 t0, sb, 8;\n and.b32 %0, %0, -16;\n or.b32 %0, %0, t0;\n}\n"
        : "+r"(ewait)
        : "r"(wa), "r"(t * RSTR + g * 16), "r"(p.N / 2 - 1), "r"(t * RSTR + 256 + g * 4), "r"(cg0), "r"(cg1), "r"(t),
          "r"(((g >> 1) + 4 * (g & 1)) * 4), "r"(nst * 8), "l"(p.ea), "l"(p.sh), "r"(p.zero), "r"(hw), "l"(p.x),
          "r"(min((int)blockIdx.x + (PFLEAD / 2 + hw) * NCTA, p.N / 2 - 1)) : "memory");
    return ewait;
}
#ifdef NOLOAD
#define TROW(J, Z0, Z1)
#else
#define TROW(J, Z0, Z1) "@l0 cp.async.bulk.tensor.3d.shared::cluster.global.mbarrier::complete_tx::bytes [xs+" STR(SM_X) "+" #J "*2048], [mp, {" #Z0 ",k" #J "," #Z1 "}], [mb];\n"
#endif
#ifdef DBG_H
#define TL "add.u32 %0, %0, c;\n"
#else
#define TL
#endif
#ifndef TCLK
#define TCLK "mov.u64 ad, %%clock64;\n cvt.u32.u64 c, ad;\n"
#endif
#define TDL "mul.hi.u32 dl, q1, rt;\n add.u32 dl, dl, %4;\n shr.u32 q0, q0, 18;\n shr.u32 q1, q1, 18;\n shr.u32 q2, q2, 18;\n shr.u32 q3, q3, 18;\n"
__device__ __forceinline__ unsigned issuer(const CUtensorMap* tm, const Params& p, int nst, unsigned T0) {
    unsigned late = 0;
    asm volatile("{\n"
        ".reg .b32 k<4>, q<4>, z<8>, xs, sa, sb, mb, dl, c, n, rt;\n .reg .b64 ad, mp;\n .reg .pred pw, pk, l0;\n"
        "mov.u32 n, " STR(SM_NEXT) ";\n ld.shared.v4.u32 {z0,z1,z2,z3}, [n+-32];\n ld.shared.v4.u32 {z4,z5,z6,z7}, [n+-16];\n"
        "ld.shared.u64 ad, [n+-48];\n add.u64 mp, ad, %1;\n ld.shared.u32 rt, [n+-40];\n add.u32 rt, rt, %5;\n"
        "mov.u32 sa, 0;\n mov.u32 xs, %2;\n mov.u32 sb, 0;\n"
        "ld.shared.v4.u32 {q0,q1,q2,q3}, [sa+" STR(SM_EID) "];\n" TDL "bra.uni TW;\n"
        "TR:\n" TL
        "elect.sync _|l0, 0xffffffff;\n"
        "shl.b32 k0, q0, 2;\n shl.b32 k1, q1, 2;\n shl.b32 k2, q2, 2;\n shl.b32 k3, q3, 2;\n add.u32 mb, sb, " STR(SM_FULL) ";\n"
        "add.u32 sa, sa, 16;\n ld.shared.v4.u32 {q0,q1,q2,q3}, [sa+" STR(SM_EID) "];\n"
        "shr.u32 sb, sa, 2;\n and.b32 sb, sb, -8;\n"
        "mbarrier.test_wait.parity.shared::cta.b64 pw, [sb+" STR(SM_EMPTY) "-8*" STR(NX) "], 0;\n"
        TROW(0, z0, z1) TROW(1, z2, z3) TROW(2, z4, z5) TROW(3, z6, z7) TCLK TDL
        "sub.u32 c, c, dl;\n setp.lt.and.u32 pw, sb, %3, pw;\n setp.ge.and.s32 pw, c, 0, pw;\n"
        "add.u32 xs, xs, 8192;\n setp.eq.u32 pk, xs, " STR(SM_R) "-" STR(SM_X) ";\n selp.b32 xs, 0, xs, pk;\n"
        "@pw bra.uni TR;\n"
        "TW:\n setp.ge.u32 pk, sb, %3;\n @pk bra.uni TEND;\n mov.u32 n, 0;\n"
        "TV:\n mbarrier.try_wait.parity.shared::cta.b64 pk, [sb+" STR(SM_EMPTY) "-8*" STR(NX) "], 0;\n"
        "add.u32 n, n, 1;\n setp.lt.and.u32 pk, n, 400000, !pk;\n @pk bra.uni TV;\n"
        "TS:\n" TCLK "sub.u32 c, c, dl;\n setp.lt.s32 pk, c, 0;\n @pk bra.uni TS;\n bra.uni TR;\n"
        "TEND:\n}\n"
        : "+r"(late)
        : "l"(tm), "r"(((NX - nst % NX) % NX) * 16384), "r"(nst * 8), "r"(T0), "r"(p.rate)
#ifdef DBG_TR
          , "l"(g_trace + blockIdx.x * 720)
#endif
        : "memory");
    return late;
}

__device__ __forceinline__ void slow_path(const Params& p) {
    const int lane = threadIdx.x & 31, warp = threadIdx.x >> 5;
#pragma unroll 1
    for (int nl = warp; nl < NPC; nl += 16) {
        const int node = blockIdx.x * NPC + nl;
        float acc[4][8];
#pragma unroll
        for (int w = 0; w < 4; w++)
#pragma unroll
            for (int j = 0; j < 8; j++) acc[w][j] = 0.f;
        if (node < p.N) {
#pragma unroll 1
            for (int e0 = 0; e0 < p.E; e0 += 32) {
                int e = e0 + lane;
                unsigned m = __ballot_sync(~0u, e < p.E && p.dst[e] == node);
                while (m) {
                    int ee = e0 + __ffs(m) - 1; m &= m - 1;
                    int s = p.src[ee];
                    float rw[8];
#pragma unroll
                    for (int j = 0; j < 8; j++) rw[j] = 0.f;
#pragma unroll 1
                    for (int k = 0; k < 16; k++) {
                        float a = __bfloat162float(p.ea[(size_t)ee * 16 + k]);
#pragma unroll
                        for (int j = 0; j < 8; j++) rw[j] += a * __bfloat162float(p.wr[k * 256 + lane * 8 + j]);
                    }
#pragma unroll 1
                    for (int u = 0; u < 4; u++) {
                        float y[8];
#pragma unroll
                        for (int j = 0; j < 8; j++) y[j] = rw[j] * __bfloat162float(p.x[((size_t)s * 4 + u) * 256 + lane * 8 + j]);
#pragma unroll
                        for (int w = 0; w < 4; w++) {
                            float a = 0.f;
#pragma unroll
                            for (int v = 0; v < 4; v++) a += __bfloat162float(p.cg[u * 16 + v * 4 + w]) * __bfloat162float(p.sh[(size_t)ee * 4 + v]);
#pragma unroll
                            for (int j = 0; j < 8; j++) acc[w][j] += a * y[j];
                        }
                    }
                }
            }
        }
#pragma unroll
        for (int w = 0; w < 4; w++) {
            int R = nl * 4 + w;
            sts128(SM_H + (lane >> 3) * HPANEL + R * 128 + (((lane & 7) ^ (R & 7)) << 4),
                   pack2(acc[w][0], acc[w][1]), pack2(acc[w][2], acc[w][3]), pack2(acc[w][4], acc[w][5]), pack2(acc[w][6], acc[w][7]));
        }
    }
}

template <int NN>
__device__ __forceinline__ void out_chunk(float* d, unsigned stg, const CUtensorMap* tmo, int wg, int row0, bool first, unsigned a, bool lead) {
    if (first) asm volatile("bar.sync %0, 128;" ::"r"(wg + 1) : "memory");
#pragma unroll
    for (int n = 0; n < NN / 8; n += 2)
        stsm4t(a + n * 1024, pack2(d[4 * n], d[4 * n + 1]), pack2(d[4 * n + 2], d[4 * n + 3]), pack2(d[4 * n + 4], d[4 * n + 5]), pack2(d[4 * n + 6], d[4 * n + 7]));
    fence_async();
    if (NN == 64) asm volatile("cp.async.bulk.wait_group.read 0;" ::: "memory");
    asm volatile("bar.sync %0, 128;" ::"r"(wg + 1) : "memory");
    if (lead) {
        tma_st(tmo, stg, wg * 64, row0);
        asm volatile("cp.async.bulk.commit_group;" ::: "memory");
    }
}

__global__ void __launch_bounds__(512, 1)
mace_kernel(const __grid_constant__ Params p, const __grid_constant__ CUtensorMap tmx, const __grid_constant__ CUtensorMap tmw,
            const __grid_constant__ CUtensorMap tmo) {
    extern __shared__ __align__(1024) char smem_raw[];
    const unsigned tstart = clk();
    const int tid = threadIdx.x, cta = blockIdx.x;
    const int e0 = cta * EPC + tid * 4;
    const bool has = tid < EPC / 4 && e0 < p.Ef;
    uint4 s4, d4;
    asm volatile("{.reg .pred q; setp.ne.u32 q, %10, 0;\n @q ld.global.nc.v4.u32 {%0,%1,%2,%3}, [%8];\n @q ld.global.nc.v4.u32 {%4,%5,%6,%7}, [%9];}"
        : "=r"(d4.x), "=r"(d4.y), "=r"(d4.z), "=r"(d4.w), "=r"(s4.x), "=r"(s4.y), "=r"(s4.z), "=r"(s4.w) : "l"(p.dst + e0), "l"(p.src + e0), "r"((int)has) : "memory");
    const int lane = tid & 31, warp = __shfl_sync(~0u, tid >> 5, 0);
    const unsigned wbar = SM_MISC, totA = SM_MISC + 80;
    bool slow = p.Ef == 0;
    int total = 0, nst = 0;
    unsigned T0 = 0, cg0 = 0, cg1 = 0, dsc[4];
    if (slow) {
        if (tid < 8) bar_init(wbar + tid * 8, 1);
    } else if (warp >= NXT / 32) {
        unsigned* const ctr = (unsigned*)(p.xch + NCTA * NCTA * NCH);
        unsigned epn;
        if (warp == 15) {
            asm volatile("ld.relaxed.gpu.global.u32 %0, [%1];" : "=r"(epn) : "l"(ctr));
        } else {
#pragma unroll
            for (int k = 0; k < 6; k++) {
                const unsigned i = lane + k * 32, c = i < CAPP / 16 + 8 || i >= CAPP / 8 + 8 ? 0xFFFFFu : 0xFFFF8u;
                sts128(i < CAPP / 8 + 8 ? SM_FULL + i * 16 : wbar + (i - CAPP / 8 - 8) * 16, c << 1, c << 11, c << 1, c << 11);
            }
            fence_async();
            __syncwarp();
            if (lane < 16) asm volatile("mbarrier.arrive.shared::cta.b64 _, [%0];" ::"r"(SM_EMPTY + (lane - 16) * 8) : "memory");
        }
        uint4 w4[8];
        unsigned c4[4];
#pragma unroll
        for (int k = 0; k < 8; k++) asm volatile("ld.global.nc.v4.u32 {%0,%1,%2,%3}, [%4];" : "=r"(w4[k].x), "=r"(w4[k].y), "=r"(w4[k].z), "=r"(w4[k].w) : "l"((const uint4*)p.wr + (tid - NXT + k * 64)));
#pragma unroll
        for (int k = 0; k < 4; k++) asm volatile("ld.global.nc.u16 %0, [%1];" : "=r"(c4[k]) : "l"(p.cg + (lane & 4) * 8 + (lane & 2) * 4 + (lane >> 3) + (k & 1) * 4 + (k & 2) * 8));
        auto put = [&]() {
#pragma unroll
            for (int k = 0; k < 8; k++) sts128(SM_WR + (warp - NXT / 32 + 2 * k) * 528 + lane * 16, w4[k].x, w4[k].y, w4[k].z, w4[k].w);
            asm volatile("prmt.b32 %0, %2, %3, 0x5410;\n prmt.b32 %1, %4, %5, 0x5410;" : "=&r"(cg0), "=r"(cg1) : "r"(c4[0]), "r"(c4[1]), "r"(c4[2]), "r"(c4[3]));
        };
        if (warp == 15) {
            epn = (epn | 255) + 1;
            sts64(totA, epn, 0);
            narrive<7, NXT + 32>();
            nsync<10, NXT + 32>();
            if (lane == 0) asm volatile("red.relaxed.gpu.global.add.u32 [%0], %1;" ::"l"(ctr), "r"(cta ? 1 : 257 - NCTA) : "memory");
            put();
            while (clk() - tstart < POLLT);
            unsigned v; int it = 0;
            do asm volatile("ld.relaxed.gpu.global.u32 %0, [%1];" : "=r"(v) : "l"(ctr) : "memory");
            while (v != epn && ++it < 4096);
            narrive<8, NXT + 32>();
#ifdef DBG_PRO
            sts32(totA + 16, it * 2);
#endif
            nsync<9, NXT + 32>();
            uint4 u[NBW];
#pragma unroll
            for (int q = 0; q < NBW; q++) u[q] = lds128(SM_BKT + (lane * NBW + q) * 16);
            const unsigned mx = lds32(SM_CNT + min(lane, NXT / 32 - 1) * 4), bad = lds32(totA + 4);
            unsigned sum = 0;
#pragma unroll
            for (int q = 0; q < NBW; q++) sum += u[q].x + u[q].y + u[q].z + u[q].w;
            unsigned inc = sum;
#pragma unroll
            for (int o = 1; o < 32; o <<= 1) asm volatile("{.reg .pred q; .reg .b32 t; shfl.sync.up.b32 t|q, %0, %1, 0, -1;\n @q add.u32 %0, %0, t;}" : "+r"(inc) : "r"(o));
            sum = inc - sum;
#pragma unroll
            for (int q = 0; q < NBW; q++) {
                const unsigned a2 = sum + u[q].x + u[q].y;
                sts128(SM_BKT + (lane * NBW + q) * 16, sum, sum + u[q].x, a2, a2 + u[q].z);
                sum = a2 + u[q].z + u[q].w;
            }
            const unsigned t0 = tstart + ((__reduce_max_sync(~0u, mx) & 0xFFF8) << 1) + T0DELTA;
            if (lane == 31) sts64(totA + 8, (inc >> 2) + bad, t0);
        } else {
            if (elect()) {
                asm volatile("prefetch.tensormap [%0];" ::"l"(&tmx) : "memory");
                asm volatile("prefetch.tensormap [%0];" ::"l"(&tmw) : "memory");
                asm volatile("prefetch.tensormap [%0];" ::"l"(&tmo) : "memory");
                if (cta < 128) pf_l2(p.wo + cta * 512, 1024);
            }
            put();
#pragma unroll
            for (int i = 0; i < PFLEAD / 2; i++) {
                if (i == PF1) while (clk() - tstart < PFT);
                if (elect()) pf_l2(p.x + (size_t)min(i * NCTA + cta, p.N / 2 - 1) * 2048, 4096);
            }
        }
        cta_sync();
        total = __shfl_sync(~0u, lds32(totA + 8), 0);
        slow = total > CAP;
        nst = (total + 7) >> 3;
    } else {
        {
            const unsigned du = DUM + (((cta * NCH + tid) & 31) << (18 + BSH));
#pragma unroll
            for (int k = 0; k < 3; k++) sts128(SM_STAGE + (tid + k * NXT) * 16, du, du, du, ~0u);
            if (tid < NCTA) sts32(SM_CNT + tid * 4, 0);
        }
        TK(24, e0);
        nsync<6, NXT>();
        TK(0, e0);
        const bool h2 = tid < NCTA * NCH - 2 * NXT;
        unsigned cc[3];
        const char* xo[3];
#pragma unroll
        for (int k = 0; k < 3; k++) {
            const unsigned i = tid + k * NXT;
            cc[k] = (i * 6554) >> 16;
            xo[k] = pin64((const char*)(p.xch + (cc[k] * ((NCTA - 1) * NCH) + cta * NCH + i)));
        }
        TK(26, d4.x);
        if (has) {
            const unsigned ss[4] = {s4.x, s4.y, s4.z, s4.w}, dd[4] = {d4.x, d4.y, d4.z, d4.w};
            unsigned c[4], o[4];
#pragma unroll
            for (int j = 0; j < 4; j++) { c[j] = __umulhi(dd[j], 0xFFFFFFFFu / NPC + 1); o[j] = atoms_add(SM_CNT + c[j] * 4, 0x15558); }
#pragma unroll
            for (int j = 0; j < 4; j++) {
                const unsigned dl = dd[j] - c[j] * NPC;
                sts32(SM_STAGE + (c[j] * (NCH * 4) + min(o[j] >> 16, NCH * 4 - 1)) * 4, (ss[j] << 18) + (tid * 4 + j) + dl * 2048 + (dl * 43 >> 8) * 4096);
            }
        }
        TK(28, e0);
        nsync<7, NXT + 32>();
        TK(1, e0);
        const unsigned ep = (lds32(totA) << 8) | 0x80000000u;
        {
            const unsigned tag = ep | (min((clk() - tstart) >> 4, 0x1FFFu) << 3);
            uint4 v[3];
#pragma unroll
            for (int k = 0; k < 3; k++) v[k] = lds128(SM_STAGE + (tid + k * NXT) * 16);
#pragma unroll
            for (int k = 0; k < 3; k++)
                if (k < 2 || h2) asm volatile(XST " [%0], {%1,%2,%3,%4};" ::"l"(xo[k]), "r"(v[k].x), "r"(v[k].y), "r"(v[k].z), "r"(tag + (v[k].w != ~0u)) : "memory");
        }
        narrive<10, NXT + 32>();
        TK(16, e0);
        if ((unsigned)__cvta_generic_to_shared(smem_raw) != SB) __trap();
        if (tid < NBW * 32 + 8) { const unsigned v = tid < NBW * 32 ? 0 : CAP * 4; sts128(SM_BKT + tid * 16, v, v, v, v); }
        if (tid < 384) { const unsigned v = tid < 381 ? (p.N - 1) << 18 : 0; sts128(SM_EID + tid * 16, v, v, v, v); }
        if (tid < 1392 / 4) sts128(SM_SRC + tid * 16, NCONS << 14, NCONS << 14, NCONS << 14, NCONS << 14);
        if (tid < 159) sts128(SM_BITS + tid * 16, 0, 0, 0, 0);
#pragma unroll
        for (int k = 0; k < 4; k++) {
            const unsigned pos = tid + k * (NCONS * 32), st = pos >> 3, j = pos & 7;
            dsc[k] = pin(pos | (((st % NX) * 8 + j) << 11) | ((((st % NR) * 8 + j) * (RSTR / 32)) << 21));
        }
        const char* const xi = pin64((const char*)(p.xch + cta * (NCTA * NCH) + tid));
        uint4 rc[3];
        rc[0].w = rc[1].w = 0;
        rc[2].w = h2 ? 0 : ep;
        rc[2].x = ~0u;
        nsync<8, NXT + 32>();
        TK(18, e0);
        {
            bool bad;
            int it = 0;
            do {
#pragma unroll
                for (int k = 0; k < 3; k++)
                    asm volatile("{.reg .pred q; .reg .b32 t; xor.b32 t, %3, %5; setp.gt.u32 q, t, 0xFFFF;\n @q ld.relaxed.gpu.global.v4.u32 {%0,%1,%2,%3}, [%4];}"
                                 : "+r"(rc[k].x), "+r"(rc[k].y), "+r"(rc[k].z), "+r"(rc[k].w) : "l"(xi + k * (NXT * 16)), "r"(ep) : "memory");
                bad = ((rc[0].w ^ ep) | (rc[1].w ^ ep) | (rc[2].w ^ ep)) > 0xFFFF;
            } while (__any_sync(~0u, bad) && ++it < 4096);
            if (bad || ((rc[0].w | rc[1].w | rc[2].w) & 1)) {
                rc[0].x = rc[1].x = rc[2].x = ~0u;
                sts32(totA + 4, CAP + 1);
            }
#ifdef DBG_PRO
            if (tid == 0) sts32(totA + 20, it * 2);
#endif
        }
        TK(2, e0);
        unsigned ord[3][3], ba[3][3], ve[3][3];
#pragma unroll
        for (int k = 0; k < 3; k++) {
            const unsigned rr[3] = {rc[k].x, rc[k].y, rc[k].z};
            if (rr[0] < DUM) {
#pragma unroll
                for (int j = 0; j < 3; j++) { ba[k][j] = pin((rr[j] >> (18 + BSH)) * 4); ord[k][j] = atoms_add(SM_BKT + ba[k][j], 4); }
            }
        }
        sts32(SM_CNT + warp * 4, __reduce_max_sync(~0u, max(rc[0].w, max(rc[1].w, rc[2].w))));
        narrive<9, NXT + 32>();
        TK(15, e0);
#pragma unroll
        for (int k = 0; k < 3; k++) {
            const unsigned rr[3] = {rc[k].x, rc[k].y, rc[k].z};
#pragma unroll
            for (int j = 0; j < 3; j++) ve[k][j] = pin((rr[j] & 0xFFFC07FF) + cc[k] * EPC);
        }
        cta_sync();
        TK(19, e0);
        total = __shfl_sync(~0u, lds32(totA + 8), 0);
        T0 = lds32(totA + 12);
#pragma unroll
        for (int k = 0; k < 3; k++) {
            if (rc[k].x < DUM) {
#pragma unroll
                for (int j = 0; j < 3; j++) ord[k][j] += lds32(SM_BKT + ba[k][j]);
#pragma unroll
                for (int j = 0; j < 3; j++)
                    asm volatile("{.reg .pred q; setp.lt.u32 q, %0, " STR(CAP) "*4;\n @q st.shared.u32 [%0+" STR(SM_EID) "], %1;}" ::"r"(ord[k][j]), "r"(ve[k][j]) : "memory");
            }
        }
        slow = total > CAP;
        if (!slow) {
            if (warp < NCONS) narrive<0, 512>();
#pragma unroll
            for (int k = 0; k < 3; k++) {
                const unsigned rr[3] = {rc[k].x, rc[k].y, rc[k].z};
                if (rr[0] < DUM) {
#pragma unroll
                    for (int j = 0; j < 3; j++)
                        asm volatile("{.reg .pred q; setp.lt.u32 q, %0, " STR(CAP) "*4;\n @q st.shared.u32 [%0+" STR(SM_SRC) "], %1;}" ::"r"(ord[k][j]), "r"(rr[j]) : "memory");
                }
            }
            if (warp == NCONS) narrive<11, NXT>();
        }
        nst = (total + 7) >> 3;
        const unsigned lim = (nst % NX) << 14;
#pragma unroll
        for (int k = 0; k < 4; k++) dsc[k] = pin(dsc[k] - lim + ((dsc[k] & 0x3C000) >= lim ? 0 : NX << 14));
        TK(20, e0);
#ifdef DBG_PRO
        if (tid == 0) { sts128(SM_NEXT + CAPP * 4, tk0, tk1, tk24, tk26); sts128(SM_NEXT + CAPP * 4 + 16, tk28, tk16, tk2, tk15); sts128(SM_NEXT + CAPP * 4 + 32, tk19, tk20, tk18, tstart); }
#endif
    }

    int wid = warp;
    if (slow) {
        asm volatile("fence.mbarrier_init.release.cluster;" ::: "memory");
        fence_async();
        cta_sync();
        if (tid < 4) { bar_expect(wbar + tid * 8, 16384); tma_2d(SB + tid * 16384, &tmw, wbar + tid * 8, tid * 64, 0); }
        slow_path(p);
    } else if (warp < NCONS) {
        nsync<11, NXT>();
        TK(3, tid);
        unsigned q[4], a[4];
        const bool k3 = warp * 32 + 3 * NCONS * 32 < total;
#pragma unroll
        for (int k = 0; k < 4; k++) if (k < 3 || k3) q[k] = lds32(SM_SRC + tid * 4 + k * (NCONS * 128));
#pragma unroll
        for (int k = 0; k < 4; k++) if (k < 3 || k3) {
            a[k] = ((q[k] >> 14) & 15) * (BW * 4) + warp * 4;
            asm volatile("red.shared.or.b32 [%0], %1;" ::"r"(SM_BITS + k * (NCONS * 4) + a[k]), "r"(1u << lane) : "memory");
        }
        __syncwarp();
#pragma unroll
        for (int k = 0; k < 4; k++) if (k < 3 || k3) a[k] = lds32(SM_BITS + k * (NCONS * 4) + a[k]);
#pragma unroll
        for (int k = 0; k < 4; k++) if (k < 3 || k3)
            sts32(SM_NEXT + k * (NCONS * 128) + ((warp * 32) | ((lane + 31 - __clz(__funnelshift_r(a[k], a[k], lane))) & 31)) * 4, dsc[k] | ((q[k] << 7) & 0x1C0000));
        asm volatile("bar.sync 5, %0;" ::"n"(NCONS * 32) : "memory");
        TK(21, tid);
        unsigned head;
        {
            const unsigned c = 31 - lane, m0 = lds32(SM_BITS + warp * (BW * 4) + c * 4), m1 = lds32(SM_BITS + warp * (BW * 4) + 128 + min(c, 12) * 4);
            const unsigned l0 = m0 ? c * 32 + 31 - __clz(m0) : CAPP - 1, l1 = m1 ? c * 32 + 1055 - __clz(m1) : CAPP - 1;
            const unsigned f0 = lds32(SM_NEXT + l0 * 4), f1 = lane ? lds32(SM_NEXT + l1 * 4) : 0x1C0000 | (warp << 21);
            const unsigned b0 = __ballot_sync(~0u, m0), b1 = __ballot_sync(~0u, m1) | 1, lt = (1u << lane) - 1;
            const unsigned h1 = __shfl_sync(~0u, f1, 31 - __clz(b1)), n1 = __shfl_sync(~0u, f1, 31 - __clz(b1 & lt));
            const unsigned h0 = __shfl_sync(~0u, f0, 31 - __clz(b0)), n0 = __shfl_sync(~0u, f0, 31 - __clz(b0 & lt));
            sts32(SM_NEXT + l0 * 4, b0 & lt ? n0 : h1);
            sts32(SM_NEXT + l1 * 4, n1);
            head = b0 ? h0 : h1;
            __syncwarp();
        }
        TK(22, tid);
#ifdef DBG_PRO
        if (tid == 0) sts128(SM_NEXT + CAPP * 4 + 48, tk3, tk21, tk22, 0);
#endif
        wid = consumer(head);
    } else if (warp == NCONS) {
        cta_sync();
        STAMPS(636 + 26, clk() | 1);
        const unsigned late = issuer(&tmx, p, nst, T0);
        wid = NCONS;
        if ((total & 7) && elect()) asm volatile("mbarrier.arrive.shared::cta.b64 _, [%0], %1;" ::"r"(SM_EMPTY + nst * 8 - 8), "r"(8 - (total & 7)) : "memory");
        STAMPS(11, clk() | 1); STAMPS(14, lds32(SM_MISC + 104)); STAMPS(12, tstart & ~1);
#pragma unroll 1
        for (int i = 0; i < 4; i++) {
            bwait(SM_EMPTY + (nst + i - NX) * 8);
            if (elect()) { bar_expect(wbar + i * 8, 16384); tma_2d(SB + i * 16384, &tmw, wbar + i * 8, i * 64, 0); }
        }
#ifdef DBG_TR
        for (int i = lane; i < nst; i += 32) g_trace[(cta * 180 + i) * 4 + 3] = lds32(SM_TR + i * 8) - T0;
#endif
#ifdef DBG_PRO
        if (lane < 15) { const unsigned ix[15] = {0, 1, 24, 26, 28, 16, 2, 15, 19, 20, 18, 31, 3, 21, 22}; unsigned j = 0;
#pragma unroll
            for (int q = 0; q < 15; q++) j = lane == q ? ix[q] : j;
            const unsigned v = lds32(SM_NEXT + CAPP * 4 + lane * 4); g_times[cta * 32 + j] = j == 31 ? v & ~1 : v | 1; }
        STAMPW(13, lds32(totA + 16)); STAMPW(17, lds32(totA + 20));
#endif
#ifdef DBG_H
        STAMPS(8, late & ~1);
#endif
        STAMPS(10, clk() | 1); STAMPS(7, T0 | 1);
    } else {
        const unsigned ewait = recorder(p, __shfl_sync(~0u, (tid >> 5) & 1, 0), nst, cg0, cg1);
        wid = NCONS + 1 + ((ewait >> 3) & 1);
#ifdef DBG_R
        if (wid == 15) STAMPW(12, ewait); else STAMPW(11, ewait);
#endif
    }

    wid = __shfl_sync(~0u, wid, 0);
    const int wg = wid >> 2, wq = wid & 3;
    int ln;
    asm volatile("mov.u32 %0, %%laneid;" : "=r"(ln));
    const bool lead = wq == 0 && ln == 0;
    unsigned af[16][4];
    const unsigned wt = SB + wg * 16384;
    const unsigned wa = wt + (((ln >> 4) * 8 + (ln & 7)) << 7) + (((2 * wq + ((ln >> 3) & 1)) ^ (ln & 7)) << 4);
    STAMPL(13);
    bwait(wbar + wg * 8);
#pragma unroll
    for (int k = 0; k < 8; k++) ldsm4t(af[k], wa + k * 2048);
    fence_async();
    cta_sync();
    STAMPL(5);
    if (lead) { bar_expect(wbar + 32 + wg * 8, 16384); tma_2d(wt, &tmw, wbar + 32 + wg * 8, wg * 64, 128); }
    const uint64_t desc0 = (uint64_t)(((SM_H) >> 4) & 0x3FFF) | (1ull << 16) | (64ull << 32) | (1ull << 62);
    float d[32];
    const int row0 = cta * (NPC * 4) + wq * 16;
    const unsigned ws = wt + wq * 2048;
    wg_fence();
#pragma unroll
    for (int k = 0; k < 8; k++) wgmma_rs<64>(d, af[k], desc0 + (k >> 2) * (HPANEL >> 4) + (k & 3) * 2, k != 0);
    wg_commit();
    bwait(wbar + 32 + wg * 8);
#pragma unroll
    for (int k = 0; k < 8; k++) ldsm4t(af[8 + k], wa + k * 2048);
    wg_fence();
#pragma unroll
    for (int k = 8; k < 16; k++) wgmma_rs<64>(d, af[k], desc0 + (k >> 2) * (HPANEL >> 4) + (k & 3) * 2, 1);
    wg_commit();
    wg_wait0();
    out_chunk<64>(d, ws, &tmo, wg, row0, true, wa, ln == 0);
#pragma unroll 1
    for (int c = 1; c < 4; c++) {
        wg_fence();
#pragma unroll
        for (int k = 0; k < 16; k++) wgmma_rs<64>(d, af[k], desc0 + c * 512 + (k >> 2) * (HPANEL >> 4) + (k & 3) * 2, k != 0);
        wg_commit();
        wg_wait0();
        out_chunk<64>(d, ws + (c & 1) * 8192, &tmo, wg, row0 + c * 64, false, wa + (c & 1) * 8192, ln == 0);
    }
    wg_fence();
#pragma unroll
    for (int k = 0; k < 16; k++) wgmma_rs<48>(d, af[k], desc0 + 4 * 512 + (k >> 2) * (HPANEL >> 4) + (k & 3) * 2, k != 0);
    wg_commit();
    wg_wait0();
    out_chunk<48>(d, ws, &tmo, wg, row0 + 256, false, wa, ln == 0 && wq < 3);
    asm volatile("cp.async.bulk.wait_group.read 0;" ::: "memory");
    STAMPL(6);
#ifdef DBG_TIMES
    if (wid == 8) STAMPS(4, clk() | 1);
    cta_sync();
    if (wid == 0 && ln >= 4 && ln < 21) g_times[cta * 32 + (ln == 12 ? 31 : ln)] = lds32(SM_BITS + ln * 4);
#endif
#ifdef DBG_GT
    { unsigned g; asm volatile("mov.u32 %0, %%globaltimer_lo;" : "=r"(g)); STAMPW(30, g & ~1); }
#endif
}

typedef CUresult (*EncFn)(CUtensorMap*, CUtensorMapDataType, cuuint32_t, void*, const cuuint64_t*, const cuuint64_t*, const cuuint32_t*,
                          const cuuint32_t*, CUtensorMapInterleave, CUtensorMapSwizzle, CUtensorMapL2promotion, CUtensorMapFloatOOBfill);

extern "C" void kernel_launch(void* const* d_in, const int* in_sizes, int n_in, void* d_out, int out_size) {
    static EncFn enc = nullptr;
    static int nsm = 0;
    static void* xch = nullptr;
    if (!enc) {
        void* fn = nullptr; cudaDriverEntryPointQueryResult qr;
        cudaGetDriverEntryPoint("cuTensorMapEncodeTiled", &fn, cudaEnableDefault, &qr);
        enc = (EncFn)fn;
        cudaGetSymbolAddress(&xch, g_xch);
        int dev = 0; cudaGetDevice(&dev);
        cudaDeviceGetAttribute(&nsm, cudaDevAttrMultiProcessorCount, dev);
        cudaFuncSetAttribute(mace_kernel, cudaFuncAttributeMaxDynamicSharedMemorySize, SM_TOTAL);
    }
    Params p;
    p.x = (const __nv_bfloat16*)d_in[0]; p.src = (const int*)d_in[1]; p.dst = (const int*)d_in[2];
    p.sh = (const __nv_bfloat16*)d_in[3]; p.ea = (const __nv_bfloat16*)d_in[4]; p.cg = (const __nv_bfloat16*)d_in[5];
    p.wr = (const __nv_bfloat16*)d_in[6]; p.wo = (const __nv_bfloat16*)d_in[7];
    p.N = in_sizes[0] / 1024; p.E = in_sizes[1];
    p.Ef = (nsm >= NCTA && p.N <= NCTA * NPC && p.E <= NCTA * EPC && p.N > 1 && (p.E & 3) == 0) ? p.E : 0;
    p.xch = (uint4*)xch;
    p.rate = (unsigned)((double)PACE * ((double)p.E / 160000.0) * 16384.0 / (double)p.N);
    p.zero = 0;
    CUtensorMap tmx, tmw, tmo;
    const cuuint32_t es[3] = {1, 1, 1};
    {
        cuuint64_t dims[3] = {64, (cuuint64_t)p.N * 4, 4}; cuuint64_t str[2] = {512, 128}; cuuint32_t box[3] = {64, 4, 4};
        enc(&tmx, CU_TENSOR_MAP_DATA_TYPE_BFLOAT16, 3, d_in[0], dims, str, box, es, CU_TENSOR_MAP_INTERLEAVE_NONE, CU_TENSOR_MAP_SWIZZLE_128B, CU_TENSOR_MAP_L2_PROMOTION_NONE, CU_TENSOR_MAP_FLOAT_OOB_FILL_NONE);
    }
    {
        cuuint64_t dims[2] = {256, 256}; cuuint64_t str[1] = {512}; cuuint32_t box[2] = {64, 128};
        enc(&tmw, CU_TENSOR_MAP_DATA_TYPE_BFLOAT16, 2, d_in[7], dims, str, box, es, CU_TENSOR_MAP_INTERLEAVE_NONE, CU_TENSOR_MAP_SWIZZLE_128B, CU_TENSOR_MAP_L2_PROMOTION_NONE, CU_TENSOR_MAP_FLOAT_OOB_FILL_NONE);
    }
    {
        cuuint64_t dims[2] = {256, (cuuint64_t)p.N * 4}; cuuint64_t str[1] = {512}; cuuint32_t box[2] = {64, 16};
        enc(&tmo, CU_TENSOR_MAP_DATA_TYPE_BFLOAT16, 2, d_out, dims, str, box, es, CU_TENSOR_MAP_INTERLEAVE_NONE, CU_TENSOR_MAP_SWIZZLE_128B, CU_TENSOR_MAP_L2_PROMOTION_NONE, CU_TENSOR_MAP_FLOAT_OOB_FILL_NONE);
    }
    const int grid = p.Ef ? NCTA : (p.N + NPC - 1) / NPC;
    mace_kernel<<<grid, 512, SM_TOTAL>>>(p, tmx, tmw, tmo);
}
```

```cpp
#include <cuda_runtime.h>
#include <cuda_bf16.h>
#include <cuda.h>
#include <stdint.h>

#ifndef NX
#define NX 10
#endif
#ifndef NR
#define NR 9
#endif
#ifndef LWG
#define LWG 1
#endif
#ifndef PACE
#define PACE 49500
#endif
#ifndef T0DELTA
#define T0DELTA 4900
#endif
#ifndef BSH
#define BSH 5
#endif
#ifndef POLLT
#define POLLT 3700
#endif
#ifndef PFT
#define PFT 5500
#endif
#ifndef PF1
#define PF1 0
#endif
#ifndef PFLEAD
#define PFLEAD 8
#endif
#ifndef RSPL
#define RSPL 10
#endif
#ifndef RLDG
#define RLDG "ld.global.nc"
#endif
#ifndef DISP
#define DISP 1
#endif
#ifndef XST
#define XST "st.relaxed.gpu.global.v4.u32"
#endif
#define NCTA 132
#define NPC 76
#define EPC 1216
#define NCH 10
#define CAP 1376
#define CAPP 1440
#define NCONS 13
#define RSTR 608
#define NBW ((((NCTA * NPC) >> BSH) + 128) / 128)

#define SB 1024
#define SM_X SB
#define SM_R (SM_X + NX * 16384)
#define SM_EID (SM_R + NR * 8 * RSTR)
#define SM_NEXT (SM_EID + 6144)
#define SM_H (SB + 65536)
#define HPANEL 38912
#define SM_FULL (SM_H + 4 * HPANEL)
#define SM_EMPTY (SM_FULL + CAPP + 128)
#define SM_SRC (SM_EMPTY + CAPP)
#define SM_BITS (SM_SRC + 1392 * 4)
#define SM_MISC (SM_BITS + 2544)
#define SM_TOTAL (SM_MISC + 128 - SB)
#define NXT 448
#define SM_STAGE SM_R
#define SM_CNT (SM_R + NXT * 48)
#define SM_WR (SM_CNT + 640)
#define SM_BKT (SM_WR + 16 * 528)
static_assert(SM_BKT + NBW * 512 + 128 <= SM_EID, "smem");
#define DUM ((unsigned)(NBW * 128) << (18 + BSH))
#define BW 45
static_assert(SM_NEXT + CAPP * 4 <= SM_FULL && SM_TOTAL <= 232448, "smem");
#define STR_(x) #x
#define STR(x) STR_(x)

__device__ uint4 g_xch[NCTA * NCTA * NCH + 8];
#ifdef DBG_TIMES
extern "C" { __device__ unsigned g_times[NCTA * 32]; }
#define STAMPV(m, i, v) asm volatile("{.reg .pred q; .reg .b32 t; .reg .b64 a, b; mov.u32 t, %%tid.x; and.b32 t, t, %0; setp.eq.u32 q, t, 0; mov.u32 t, %%ctaid.x; mov.u64 b, g_times; mad.wide.u32 a, t, 128, b; @q st.global.u32 [a+%1], %2;}" ::"n"(m), "n"((i) * 4), "r"(v) : "memory")
#define STAMP(i) STAMPV(1023, i, clk() | 0x1)
#define STAMPS(i, v) sts32(SM_BITS + (i) * 4, v)
#define STAMPL(i) if (wid == 0) STAMPS(i, clk() | 0x1)
#define STAMPW(i, v) asm volatile("{.reg .b32 t; .reg .b64 a, b; mov.u32 t, %%ctaid.x; mov.u64 b, g_times; mad.wide.u32 a, t, 128, b; st.global.u32 [a+%0], %1;}" ::"n"((i) * 4), "r"(v) : "memory")
#define TK(i, dep) unsigned tk##i; asm volatile("{.reg .b32 t; and.b32 t, %1, %2; mov.u32 %0, %%clock; add.u32 %0, %0, t;}" : "=r"(tk##i) : "r"(dep), "r"(p.zero) : "memory")
#define TKO(i) STAMPV(1023, i, tk##i | 1)
#ifndef DBG_PRO
#undef TK
#define TK(i, dep)
#endif
#else
#define STAMP(i)
#define STAMPL(i)
#define STAMPS(i, v)
#define STAMPV(m, i, v)
#define STAMPW(i, v)
#define TK(i, dep)
#define TKO(i)
#endif

struct Params {
    const int* src; const int* dst; uint4* xch; const __nv_bfloat16* wr;
    int Ef, N;
    const __nv_bfloat16* cg; const __nv_bfloat16* x; const __nv_bfloat16* sh; const __nv_bfloat16* ea; const __nv_bfloat16* wo;
    int E; unsigned rate, zero;
};

__device__ __forceinline__ unsigned clk() { unsigned c; asm volatile("mov.u32 %0, %%clock;" : "=r"(c)); return c; }
__device__ __forceinline__ bool elect() { unsigned p; asm volatile("{.reg .pred P; elect.sync _|P, 0xffffffff; selp.u32 %0,1,0,P;}" : "=r"(p)); return p; }
__device__ __forceinline__ bool try_wait(unsigned a) { unsigned ok; asm volatile("{.reg .pred p; mbarrier.try_wait.parity.shared::cta.b64 p,[%1],0; selp.u32 %0,1,0,p;}" : "=r"(ok) : "r"(a) : "memory"); return ok; }
__device__ __forceinline__ void bwait(unsigned a) { if (!try_wait(a)) { for (int i = 0; i < (1 << 18) && !try_wait(a); i++); } }
__device__ __forceinline__ unsigned pin(unsigned x) { unsigned y; asm volatile("mov.u32 %0, %1;" : "=r"(y) : "r"(x)); return y; }
__device__ __forceinline__ const char* pin64(const char* x) { const char* y; asm volatile("mov.u64 %0, %1;" : "=l"(y) : "l"(x)); return y; }
__device__ __forceinline__ void split(unsigned x, unsigned c) { asm volatile("{.reg .pred p; setp.eq.u32 p, %0, %1; @p exit;}" ::"r"(x), "r"(c) : "memory"); }
__device__ __forceinline__ void bar_init(unsigned a, unsigned c) { asm volatile("mbarrier.init.shared::cta.b64 [%0], %1;" ::"r"(a), "r"(c) : "memory"); }
__device__ __forceinline__ void bar_expect(unsigned a, unsigned bytes) { asm volatile("mbarrier.arrive.expect_tx.shared::cta.b64 _, [%0], %1;" ::"r"(a), "r"(bytes) : "memory"); }
__device__ __forceinline__ void bar_complete(unsigned a, unsigned bytes) { asm volatile("mbarrier.complete_tx.relaxed.cta.shared::cta.b64 [%0], %1;" ::"r"(a), "r"(bytes) : "memory"); }
__device__ __forceinline__ void fence_async() { asm volatile("fence.proxy.async.shared::cta;" ::: "memory"); }
template <int ID, int N> __device__ __forceinline__ void nsync() { asm volatile("bar.sync %0, %1;" ::"n"(ID), "n"(N) : "memory"); }
template <int ID, int N> __device__ __forceinline__ void narrive() { asm volatile("bar.arrive %0, %1;" ::"n"(ID), "n"(N) : "memory"); }
__device__ __forceinline__ void cta_sync() { asm volatile("bar.sync 0, 512;" ::: "memory"); }
__device__ __forceinline__ unsigned lds32(unsigned a) { unsigned v; asm volatile("ld.shared.u32 %0,[%1];" : "=r"(v) : "r"(a) : "memory"); return v; }
__device__ __forceinline__ unsigned lds16(unsigned a) { unsigned v; asm volatile("ld.shared.u16 %0,[%1];" : "=r"(v) : "r"(a) : "memory"); return v; }
__device__ __forceinline__ uint4 lds128(unsigned a) { uint4 v; asm volatile("ld.shared.v4.u32 {%0,%1,%2,%3},[%4];" : "=r"(v.x), "=r"(v.y), "=r"(v.z), "=r"(v.w) : "r"(a) : "memory"); return v; }
__device__ __forceinline__ void sts32(unsigned a, unsigned v) { asm volatile("st.shared.u32 [%0],%1;" ::"r"(a), "r"(v) : "memory"); }
__device__ __forceinline__ void sts16(unsigned a, unsigned v) { asm volatile("st.shared.u16 [%0],%1;" ::"r"(a), "r"(v) : "memory"); }
__device__ __forceinline__ void sts64(unsigned a, unsigned x, unsigned y) { asm volatile("st.shared.v2.u32 [%0],{%1,%2};" ::"r"(a), "r"(x), "r"(y) : "memory"); }
__device__ __forceinline__ void sts128(unsigned a, unsigned x, unsigned y, unsigned z, unsigned w) { asm volatile("st.shared.v4.u32 [%0],{%1,%2,%3,%4};" ::"r"(a), "r"(x), "r"(y), "r"(z), "r"(w) : "memory"); }
__device__ __forceinline__ unsigned atoms_add(unsigned a, unsigned v) { unsigned o; asm volatile("atom.shared.add.u32 %0,[%1],%2;" : "=r"(o) : "r"(a), "r"(v) : "memory"); return o; }
__device__ __forceinline__ void ldsm4t(unsigned* r, unsigned a) { asm volatile("ldmatrix.sync.aligned.m8n8.x4.trans.shared.b16 {%0,%1,%2,%3},[%4];" : "=r"(r[0]), "=r"(r[1]), "=r"(r[2]), "=r"(r[3]) : "r"(a) : "memory"); }
__device__ __forceinline__ void stsm4t(unsigned a, unsigned r0, unsigned r1, unsigned r2, unsigned r3) { asm volatile("stmatrix.sync.aligned.m8n8.x4.trans.shared.b16 [%0],{%1,%2,%3,%4};" ::"r"(a), "r"(r0), "r"(r1), "r"(r2), "r"(r3) : "memory"); }
__device__ __forceinline__ unsigned pack2(float lo, float hi) { unsigned p; asm("cvt.rn.bf16x2.f32 %0,%1,%2;" : "=r"(p) : "f"(hi), "f"(lo)); return p; }
__device__ __forceinline__ void mma1688(float* d, unsigned a0, unsigned a1, unsigned b0) {
    asm("mma.sync.aligned.m16n8k8.row.col.f32.bf16.bf16.f32 {%0,%1,%2,%3},{%4,%5},{%6},{%7,%7,%7,%7};"
        : "=f"(d[0]), "=f"(d[1]), "=f"(d[2]), "=f"(d[3]) : "r"(a0), "r"(a1), "r"(b0), "f"(0.f));
}
__device__ __forceinline__ void mma16816(float* d, const unsigned* a, unsigned b0, unsigned b1) {
    asm volatile("mma.sync.aligned.m16n8k16.row.col.f32.bf16.bf16.f32 {%0,%1,%2,%3},{%4,%5,%6,%7},{%8,%9},{%10,%10,%10,%10};"
        : "=f"(d[0]), "=f"(d[1]), "=f"(d[2]), "=f"(d[3]) : "r"(a[0]), "r"(a[1]), "r"(a[2]), "r"(a[3]), "r"(b0), "r"(b1), "f"(0.f));
}
__device__ __forceinline__ void tma_x(unsigned da, const void* tm, unsigned ba, int c1) {
    asm volatile("cp.async.bulk.tensor.3d.shared::cluster.global.mbarrier::complete_tx::bytes [%0], [%1, {%3,%4,%3}], [%2];" ::"r"(da), "l"(tm), "r"(ba), "r"(0), "r"(c1) : "memory");
}
__device__ __forceinline__ void tma_2d(unsigned da, const CUtensorMap* tm, unsigned ba, int c0, int c1) {
    asm volatile("cp.async.bulk.tensor.2d.shared::cluster.global.mbarrier::complete_tx::bytes [%0], [%1, {%3,%4}], [%2];" ::"r"(da), "l"(tm), "r"(ba), "r"(c0), "r"(c1) : "memory");
}
__device__ __forceinline__ void tma_st(const CUtensorMap* tm, unsigned sa, int c0, int c1) {
    asm volatile("cp.async.bulk.tensor.2d.global.shared::cta.bulk_group [%0, {%2,%3}], [%1];" ::"l"(tm), "r"(sa), "r"(c0), "r"(c1) : "memory");
}
__device__ __forceinline__ void pf_l2(const void* p, unsigned bytes) { asm volatile("cp.async.bulk.prefetch.L2.global [%0], %1;" ::"l"(p), "r"(bytes) : "memory"); }

#define WG_REGS24(d) "+f"(d[0]), "+f"(d[1]), "+f"(d[2]), "+f"(d[3]), "+f"(d[4]), "+f"(d[5]), "+f"(d[6]), "+f"(d[7]), \
    "+f"(d[8]), "+f"(d[9]), "+f"(d[10]), "+f"(d[11]), "+f"(d[12]), "+f"(d[13]), "+f"(d[14]), "+f"(d[15]), \
    "+f"(d[16]), "+f"(d[17]), "+f"(d[18]), "+f"(d[19]), "+f"(d[20]), "+f"(d[21]), "+f"(d[22]), "+f"(d[23])
template <int NN> __device__ __forceinline__ void wgmma_rs(float* d, const unsigned* a, uint64_t desc, int scale_d);
template <> __device__ __forceinline__ void wgmma_rs<48>(float* d, const unsigned* a, uint64_t desc, int scale_d) {
    asm volatile("{.reg .pred p; setp.ne.b32 p, %29, 0;\n"
        "wgmma.mma_async.sync.aligned.m64n48k16.f32.bf16.bf16 {%0,%1,%2,%3,%4,%5,%6,%7,%8,%9,%10,%11,%12,%13,%14,%15,%16,%17,%18,%19,"
        "%20,%21,%22,%23}, {%24,%25,%26,%27}, %28, p, 1, 1, 0;}"
        : WG_REGS24(d)
        : "r"(a[0]), "r"(a[1]), "r"(a[2]), "r"(a[3]), "l"(desc), "r"(scale_d));
}
template <> __device__ __forceinline__ void wgmma_rs<64>(float* d, const unsigned* a, uint64_t desc, int scale_d) {
    asm volatile("{.reg .pred p; setp.ne.b32 p, %37, 0;\n"
        "wgmma.mma_async.sync.aligned.m64n64k16.f32.bf16.bf16 {%0,%1,%2,%3,%4,%5,%6,%7,%8,%9,%10,%11,%12,%13,%14,%15,%16,%17,%18,%19,"
        "%20,%21,%22,%23,%24,%25,%26,%27,%28,%29,%30,%31}, {%32,%33,%34,%35}, %36, p, 1, 1, 0;}"
        : WG_REGS24(d), "+f"(d[24]), "+f"(d[25]), "+f"(d[26]), "+f"(d[27]), "+f"(d[28]), "+f"(d[29]), "+f"(d[30]), "+f"(d[31])
        : "r"(a[0]), "r"(a[1]), "r"(a[2]), "r"(a[3]), "l"(desc), "r"(scale_d));
}
__device__ __forceinline__ void wg_fence() { asm volatile("wgmma.fence.sync.aligned;" ::: "memory"); }
__device__ __forceinline__ void wg_commit() { asm volatile("wgmma.commit_group.sync.aligned;" ::: "memory"); }
__device__ __forceinline__ void wg_wait0() { asm volatile("wgmma.wait_group.sync.aligned 0;" ::: "memory"); }

#define PF(D, RW, K, J0, J1) \
    "cvt.rn.bf16x2.f32 t0, " #D "1, " #D "0;\n cvt.rn.bf16x2.f32 t1, " #D "3, " #D "2;\n" \
    "mov.b32 {lo, hi}, " #RW ";\n mov.b32 u0, {lo, lo};\n mov.b32 u1, {hi, hi};\n" \
    "fma.rn.bf16x2 a" #K "_" #J0 ", t0, u0, a" #K "_" #J0 ";\n fma.rn.bf16x2 a" #K "_" #J1 ", t1, u1, a" #K "_" #J1 ";\n"
#define MMA(D, A0, A1) "mma.sync.aligned.m16n8k8.row.col.f32.bf16.bf16.f32 {" #D "0," #D "1," #D "2," #D "3}, {" #A0 "," #A1 "}, {bf}, {fz,fz,fz,fz};\n"
#define LDX(X, OFF) "ldmatrix.sync.aligned.m8n8.x4.trans.shared.b16 {" #X "0," #X "1," #X "2," #X "3}, [xa+" STR(SM_X) "+" #OFF "];\n"
#define DECODE \
    "lop3.b32 xa, dn, 0x3F800, %1, 0xEA;\n" \
    "shr.u32 t2, dn, 21;\n mad.lo.u32 ra, t2, 32, %2;\n mad.lo.u32 ca, t2, 32, %3;\n" \
    "and.b32 t3, dn, 0x7FF;\n shl.b32 t3, t3, 2;\n" SETD
#define LOADS \
    LDX(x, 0) "@act ld.shared.u32 bf, [ca+" STR(SM_R) "];\n" LDX(y, 512) LDR(r, 0) \
    "ld.shared.u32 dn, [t3+" STR(SM_NEXT) "];\n"
#if DISP == 0
#define SETD "bfe.u32 ix, dn, 18, 3;\n"
#define DISPATCH "brx.idx.uni ix, TS;\n"
#define T23
#define T45
#else
#define SETD "and.b32 ix, dn, 0x40000;\n setp.ne.u32 q0, ix, 0;\n and.b32 ix, dn, 0x80000;\n setp.ne.u32 q1, ix, 0;\n and.b32 ix, dn, 0x100000;\n setp.ne.u32 q2, ix, 0;\n"
#define DISPATCH "@q2 bra.uni T45;\n @q1 bra.uni T23;\n @q0 bra.uni B1;\n bra.uni B0;\n"
#define T23 "T23:\n @q0 bra.uni B3;\n"
#define T45 "T45:\n @q1 bra.uni FIN;\n @q0 bra.uni B5;\n"
#endif
#define LDR(R, OFF) "ld.shared.v4.u32 {" #R "0," #R "1," #R "2," #R "3}, [ra+" STR(SM_R) "+" #OFF "];\n"
#ifdef JG
#define JIG "and.b32 t0, t0, 0xFFFF;\n"
#else
#define JIG
#endif
#define BODY(K) "B" #K ":\n" \
    MMA(d, x0, x1) MMA(e, x2, x3) LDX(x, 1024) "and.b32 bn, dn, 0x7F8;\n" \
    "mbarrier.test_wait.parity.shared::cta.b64 p, [bn+" STR(SM_FULL) "], 0;\n" \
    PF(d, r0, K, 0, 1) MMA(d, y0, y1) PF(e, r1, K, 2, 3) MMA(e, y2, y3) LDX(y, 1536) LDR(s, 128) \
    PF(d, r2, K, 4, 5) MMA(d, x0, x1) PF(e, r3, K, 6, 7) MMA(e, x2, x3) \
    PF(d, s0, K, 8, 9) MMA(d, y0, y1) \
    "@l0 mbarrier.arrive.shared::cta.b64 _, [bc+" STR(SM_EMPTY) "];\n" \
    PF(e, s1, K, 10, 11) MMA(e, y2, y3) \
    "mov.u32 bc, bn;\n" DECODE \
    "@!p bra.uni W" #K ";\n" \
    "R" #K ":\n" LOADS \
    PF(d, s2, K, 12, 13) PF(e, s3, K, 14, 15) DISPATCH
#ifdef DBG_TR
#define SM_TR (SM_NEXT + CAPP * 4)
#define TRC "mov.u32 t1, %%clock;\n st.shared.u32 [bc+" STR(SM_TR) "], t1;\n"
extern "C" { __device__ unsigned g_trace[NCTA * 4 * 180]; }
#else
#define TRC
#endif
#define WAIT(K) "W" #K ":\n mov.u32 t0, 0;\n" \
    "V" #K ":\n mbarrier.try_wait.parity.shared::cta.b64 p, [bc+" STR(SM_FULL) "], 0;\n" TRC "@p bra.uni R" #K ";\n" \
    "add.u32 t0, t0, 1;\n setp.lt.u32 p, t0, 400000;\n @p bra.uni V" #K ";\n bra.uni R" #K ";\n"
#define Z4(K, A, B, C, D) "mov.u32 a" #K "_" #A ", 0; mov.u32 a" #K "_" #B ", 0; mov.u32 a" #K "_" #C ", 0; mov.u32 a" #K "_" #D ", 0;\n"
#define ZACC(K) Z4(K, 0, 1, 2, 3) Z4(K, 4, 5, 6, 7) Z4(K, 8, 9, 10, 11) Z4(K, 12, 13, 14, 15)
#define ST4(K, A, B, C, D, R, P) "stmatrix.sync.aligned.m8n8.x4.trans.shared.b16 [" #R "+" STR(SM_H) "+" #K "*512+" #P "*" STR(HPANEL) "], {a" #K "_" #A ",a" #K "_" #B ",a" #K "_" #C ",a" #K "_" #D "};\n"
#define STP(P, A, B, C, D, R0, R1) ST4(0, A, B, C, D, R0, P) ST4(1, A, B, C, D, R1, P) ST4(2, A, B, C, D, R0, P) ST4(3, A, B, C, D, R1, P) \
    "@q0 bra.uni E" #P ";\n" ST4(4, A, B, C, D, R0, P) ST4(5, A, B, C, D, R1, P) "E" #P ":\n"
#define FS(P) "add.u32 t2, bn, " STR(SM_H) "-" STR(SM_X) "+" #P "*" STR(HPANEL) ";\n shr.u32 t2, t2, 14;\n mad.lo.u32 t2, t2, 8, bc;\n"
#define FW(ID, PRE, A) "@q1 bra.uni G" #ID ";\n" PRE "mov.u32 t3, 0;\n" \
    "F" #ID ":\n mbarrier.try_wait.parity.shared::cta.b64 p, [" #A "+" STR(SM_EMPTY) "-8*" STR(NX) "], 0;\n vote.sync.all.pred p, p, -1;\n" \
    "add.u32 t3, t3, 1;\n setp.lt.and.u32 p, t3, 400000, !p;\n @p bra.uni F" #ID ";\n G" #ID ":\n"
__device__ __forceinline__ unsigned consumer(unsigned head) {
    const int lane = threadIdx.x & 31, g = lane >> 2, t = lane & 3;
    const unsigned xl = (lane & 3) * 128 + ((((lane >> 3) + (lane & 4)) ^ (lane & 3)) << 4);
    const unsigned rl = (t >> 1) * 320 + g * 16;
    const unsigned cl = (t >> 1) == (g >> 2) ? 256 + (2 * (g & 3) + (t & 1)) * 4 : 0;
    asm volatile("{\n"
        ".reg .b32 a0_<16>, a1_<16>, a2_<16>, a3_<16>, a4_<16>, a5_<16>;\n"
        ".reg .b32 x<4>, y<4>, r<4>, s<4>, t<4>, u<2>, bf, xa, ra, ca, bn, bc, dn, ix;\n"
        ".reg .f32 d<4>, e<4>, fz;\n .reg .b16 lo, hi;\n .reg .pred p, q<3>, act, l0;\n"
#if DISP == 0
        "TS: .branchtargets B0, B1, B2, B3, B4, B5, FIN, FIN;\n"
#endif
        "mov.f32 fz, 0f00000000;\n mov.u32 bf, 0;\n setp.ne.u32 act, %3, 0;\n setp.eq.u32 l0, %1, 0;\n mov.u32 dn, %0;\n"
        ZACC(0) ZACC(1) ZACC(2) ZACC(3) ZACC(4) ZACC(5)
        "and.b32 bc, dn, 0x7F8;\n"
        DECODE "and.b32 t0, dn, 0x1C0000;\n setp.eq.u32 p, t0, 0x1C0000;\n @p bra.uni FIN;\n"
        WAIT(6)
        "R6:\n" LOADS DISPATCH
        BODY(0) BODY(1) T23 BODY(2) BODY(3) T45 BODY(4) BODY(5)
        WAIT(0) WAIT(1) WAIT(2) WAIT(3) WAIT(4) WAIT(5)
        "FIN:\n mov.u32 bc, " STR(SM_MISC) ";\n ld.shared.u32 bc, [bc+88];\n add.u32 bc, bc, 7;\n and.b32 bc, bc, -8;\n"
        "mov.u32 t2, %%laneid;\n min.u32 ca, t2, " STR(NX) "-1;\n mad.lo.u32 ca, ca, 8, bc;\n"
        "mbarrier.test_wait.parity.shared::cta.b64 p, [ca+" STR(SM_EMPTY) "-8*" STR(NX) "], 0;\n vote.sync.all.pred q1, p, -1;\n"
        "sub.u32 t0, ra, %2;\n" JIG "shr.u32 %0, t0, 5;\n mul.lo.u32 bn, t0, 96;\n"
        "add.u32 t0, bn, %1;\n xor.b32 t1, t0, 64;\n setp.eq.u32 q0, %0, 12;\n vote.sync.all.pred q0, q0, -1;\n and.b32 t2, t2, 1;\n mad.lo.u32 bn, t2, 3071, bn;\n"
        FW(0, FS(0), t2) STP(0, 0, 1, 2, 3, t0, t1) FW(1, FS(1), t2) STP(1, 4, 5, 6, 7, t1, t0) FW(2, , ca)
#ifdef DBG_TIMES
        "mov.u32 t2, %%clock;\n or.b32 t2, t2, 1;\n mov.u32 t3, " STR(SM_BITS) ";\n st.shared.u32 [t3+36], t2;\n"
#endif
        STP(2, 8, 9, 10, 11, t0, t1) STP(3, 12, 13, 14, 15, t1, t0)
        "}\n" : "+r"(head) : "r"(xl), "r"(rl), "r"(cl) : "memory");
    return head;
}

#define RMMA(D, Q, B0, B1) "mma.sync.aligned.m16n8k16.row.col.f32.bf16.bf16.f32 {" #D "0," #D "1," #D "2," #D "3}, {w" #Q "_0,w" #Q "_1,w" #Q "_2,w" #Q "_3}, {" #B0 "," #B1 "}, {fz,fz,fz,fz};\n"
#define RPK(I, D) "cvt.rn.bf16x2.f32 u" #I ", " #D "2, " #D "0;\n cvt.rn.bf16x2.f32 v" #I ", " #D "3, " #D "1;\n"
#define RG(Q0, Q1, Q2, Q3, B0, B1, A, OFF) \
    RMMA(da, Q0, B0, B1) RMMA(db, Q1, B0, B1) RMMA(dc, Q2, B0, B1) RMMA(dd, Q3, B0, B1) \
    RPK(0, da) RPK(1, db) RPK(2, dc) RPK(3, dd) \
    "st.shared.v4.u32 [" #A "+" #OFF "], {u0,u1,u2,u3};\n st.shared.v4.u32 [" #A "+" #OFF "+4*" STR(RSTR) "], {v0,v1,v2,v3};\n"
#define RSPLIT(M) "setp.eq.u32 pk, ro, " #M ";\n @pk exit;\n"
#if RSPL & 2
#define RS1 RSPLIT(1)
#else
#define RS1
#endif
#if RSPL & 4
#define RS2 RSPLIT(2)
#else
#define RS2
#endif
#if RSPL & 8
#define RS3 RSPLIT(3)
#else
#define RS3
#endif
#ifdef NOLOAD
#define RTX "0"
#else
#define RTX "16384"
#endif
#ifdef DBG_R
#define RW0 "mov.u32 tw, %%clock;\n"
#define RW1 "mov.u32 t0, %%clock;\n sub.u32 t0, t0, tw;\n add.u32 %0, %0, t0;\n"
#else
#define RW0
#define RW1
#endif
#ifdef XREC
#define RG2(B0, B1)
#else
#define RG2(B0, B1) RG(8, 9, 10, 11, B0, B1, a0, 128) RS3 RG(12, 13, 14, 15, B0, B1, a0, 448)
#endif
#define RSTAGE(ID, B0, B1, SEL, PRE, MID) \
    "@!pw bra.uni RW" #ID ";\n RR" #ID ":\n" PRE \
    "mbarrier.test_wait.parity.shared::cta.b64 pw, [sb+" STR(SM_EMPTY) "+16-8*" STR(NR) "], 0;\n" \
    "add.u32 a0, ro, %2;\n add.u32 a2, ro, %4;\n" \
    RG(0, 1, 2, 3, B0, B1, a0, 0) RS1 RG(4, 5, 6, 7, B0, B1, a0, 320) RS2 MID \
    "selp.b32 t0, " SEL ", pe;\n" \
    "mma.sync.aligned.m16n8k8.row.col.f32.bf16.bf16.f32 {da0,da1,da2,da3}, {%5,%6}, {t0}, {fz,fz,fz,fz};\n" RPK(0, da) \
    "st.shared.u32 [a2], u0;\n st.shared.u32 [a2+4*" STR(RSTR) "], v0;\n" \
    RG2(B0, B1) \
    "bar.warp.sync 0xffffffff;\n elect.sync _|l0, 0xffffffff;\n" \
    "@l0 mbarrier.arrive.expect_tx.shared::cta.b64 _, [sb+" STR(SM_FULL) "], " RTX ";\n" \
    "add.u32 sb, sb, 16;\n add.u32 ro, ro, 16*" STR(RSTR) ";\n setp.ge.u32 pk, ro, " STR(SM_EID) ";\n @pk sub.u32 ro, ro, 8*" STR(NR) "*" STR(RSTR) ";\n" \
    "setp.ge.u32 pk, sb, %9;\n @pk bra.uni REND;\n"
#define RWAIT(ID) "RW" #ID ":\n" RW0 "mov.u32 t1, 0;\n" \
    "RV" #ID ":\n mbarrier.try_wait.parity.shared::cta.b64 pk, [sb+" STR(SM_EMPTY) "-8*" STR(NR) "], 0;\n" \
    "add.u32 t1, t1, 1;\n setp.lt.and.u32 pk, t1, 400000, !pk;\n @pk bra.uni RV" #ID ";\n" RW1 "bra.uni RR" #ID ";\n"
#define RLD1(S, I, J, E) "shl.b32 " #E ", " #E ", 2;\n lop3.b32 " #E ", " #E ", 0xFFFFC, tt, 0xEA;\n mad.wide.u32 ad, " #E ", 8, %10;\n " RLDG ".v2.u32 {" #S #I "," #S #J "}, [ad];\n"
#define RLD2(S, I, E, F) "selp.b32 t1, " #E ", " #F ", pe;\n and.b32 t1, t1, -2;\n mad.wide.u32 ad, t1, 2, %11;\n " RLDG ".u32 " #S #I ", [ad];\n"
#define RLOAD(S, DEP) "lop3.b32 tt, " #DEP ", %12, %7, 0xEA;\n" \
    RLD1(S, 0, 1, e0) RLD1(S, 2, 3, e1) RLD2(S, 8, e0, e1) RLD1(S, 4, 5, e2) RLD1(S, 6, 7, e3) RLD2(S, 9, e2, e3)
#define REID1(I) "ld.shared.u32 e" #I ", [ea+" STR(SM_EID) "+64*" #I "];\n"
#define REID REID1(0) REID1(1) REID1(2) REID1(3) "add.u32 ea, ea, 256;\n"
#define RPF "mad.wide.u32 ad, pf, 4096, %14;\n add.u32 pf, pf, 2*" STR(NCTA) ";\n setp.lt.u32 pk, pf, %3;\n selp.b32 pf, pf, %3, pk;\n" \
    "elect.sync _|l0, 0xffffffff;\n @l0 cp.async.bulk.prefetch.L2.global [ad], 4096;\n"
#define RLDW(Q) "ldmatrix.sync.aligned.m8n8.x4.trans.shared.b16 {w" #Q "_0,w" #Q "_1,w" #Q "_2,w" #Q "_3}, [%1+2*(64*(2*(" #Q ">>3)+((" #Q "&3)>>1))+8*((2*(" #Q "&1)+(" #Q "&4))^(2*(" #Q "&2))))];\n"
__device__ __forceinline__ unsigned recorder(const Params& p, int hw, int nst, unsigned cg0, unsigned cg1) {
    const int lane = threadIdx.x & 31, g = lane >> 2, t = lane & 3, mi = lane >> 3, r = lane & 7;
    const unsigned wa = SM_WR + (4 * (r >> 1) + (r & 1) + 2 * (mi >> 1)) * 528 + (mi & 1) * 16;
    unsigned ewait = 0;
    asm volatile("{\n"
        ".reg .b32 w0_<4>, w1_<4>, w2_<4>, w3_<4>, w4_<4>, w5_<4>, w6_<4>, w7_<4>, w8_<4>, w9_<4>, w10_<4>, w11_<4>, w12_<4>, w13_<4>, w14_<4>, w15_<4>;\n"
        ".reg .b32 x<10>, y<10>, e<4>, u<4>, v<4>, a<3>, t<2>, tt, tw, ea, sb, ro, pf;\n .reg .b64 ad;\n"
        ".reg .f32 da<4>, db<4>, dc<4>, dd<4>, fz;\n .reg .pred pw, pk, pe, l0;\n"
        RLDW(0) RLDW(1) RLDW(2) RLDW(3) RLDW(4) RLDW(5) RLDW(6) RLDW(7) RLDW(8) RLDW(9) RLDW(10) RLDW(11) RLDW(12) RLDW(13) RLDW(14) RLDW(15)
        "mov.f32 fz, 0f00000000;\n and.b32 t0, %7, 1;\n setp.eq.u32 pe, t0, 0;\n"
        "mov.u32 pf, %15;\n mad.lo.u32 ea, %13, 32, %8;\n shl.b32 sb, %13, 3;\n mad.lo.u32 ro, %13, 8*" STR(RSTR) ", " STR(SM_R) ";\n"
        "bar.sync 0, 512;\n"
        "setp.lt.u32 pw, sb, %9;\n @!pw bra.uni REND;\n"
        REID RLOAD(x, %12) REID
        "RTOP:\n"
        RSTAGE(0, x0, x1, "x8, 0", RLOAD(y, x0), ) RSTAGE(1, x2, x3, "0, x8", , ) RSTAGE(2, x4, x5, "x9, 0", , RPF) RSTAGE(3, x6, x7, "0, x9", , REID)
        RSTAGE(4, y0, y1, "y8, 0", RLOAD(x, y0), ) RSTAGE(5, y2, y3, "0, y8", , ) RSTAGE(6, y4, y5, "y9, 0", , RPF) RSTAGE(7, y6, y7, "0, y9", , REID)
        "bra.uni RTOP;\n"
        RWAIT(0) RWAIT(1) RWAIT(2) RWAIT(3) RWAIT(4) RWAIT(5) RWAIT(6) RWAIT(7)
        "REND:\n and.b32 t0, sb, 8;\n and.b32 %0, %0, -16;\n or.b32 %0, %0, t0;\n}\n"
        : "+r"(ewait)
        : "r"(wa), "r"(t * RSTR + g * 16), "r"(p.N / 2 - 1), "r"(t * RSTR + 256 + g * 4), "r"(cg0), "r"(cg1), "r"(t),
          "r"(((g >> 1) + 4 * (g & 1)) * 4), "r"(nst * 8), "l"(p.ea), "l"(p.sh), "r"(p.zero), "r"(hw), "l"(p.x),
          "r"(min((int)blockIdx.x + (PFLEAD / 2 + hw) * NCTA, p.N / 2 - 1)) : "memory");
    return ewait;
}
#ifdef NOLOAD
#define TROW(J, Z0, Z1)
#else
#define TROW(J, Z0, Z1) "@l0 cp.async.bulk.tensor.3d.shared::cluster.global.mbarrier::complete_tx::bytes [xs+" STR(SM_X) "+" #J "*2048], [mp, {" #Z0 ",k" #J "," #Z1 "}], [mb];\n"
#endif
#ifdef DBG_H
#define TL "add.u32 %0, %0, c;\n"
#else
#define TL
#endif
#ifndef TCLK
#define TCLK "mov.u64 ad, %%clock64;\n cvt.u32.u64 c, ad;\n"
#endif
#define TDL "mul.hi.u32 dl, q1, rt;\n add.u32 dl, dl, %4;\n shr.u32 q0, q0, 18;\n shr.u32 q1, q1, 18;\n shr.u32 q2, q2, 18;\n shr.u32 q3, q3, 18;\n"
__device__ __forceinline__ unsigned issuer(const CUtensorMap* tm, const Params& p, int nst, unsigned T0) {
    unsigned late = 0;
    asm volatile("{\n"
        ".reg .b32 k<4>, q<4>, z<8>, xs, sa, sb, mb, dl, c, n, rt;\n .reg .b64 ad, mp;\n .reg .pred pw, pk, l0;\n"
        "mov.u32 n, " STR(SM_NEXT) ";\n ld.shared.v4.u32 {z0,z1,z2,z3}, [n+-32];\n ld.shared.v4.u32 {z4,z5,z6,z7}, [n+-16];\n"
        "ld.shared.u64 ad, [n+-48];\n add.u64 mp, ad, %1;\n ld.shared.u32 rt, [n+-40];\n add.u32 rt, rt, %5;\n"
        "mov.u32 sa, 0;\n mov.u32 xs, %2;\n mov.u32 sb, 0;\n"
        "ld.shared.v4.u32 {q0,q1,q2,q3}, [sa+" STR(SM_EID) "];\n" TDL "bra.uni TW;\n"
        "TR:\n" TL
        "elect.sync _|l0, 0xffffffff;\n"
        "shl.b32 k0, q0, 2;\n shl.b32 k1, q1, 2;\n shl.b32 k2, q2, 2;\n shl.b32 k3, q3, 2;\n add.u32 mb, sb, " STR(SM_FULL) ";\n"
        "add.u32 sa, sa, 16;\n ld.shared.v4.u32 {q0,q1,q2,q3}, [sa+" STR(SM_EID) "];\n"
        "shr.u32 sb, sa, 2;\n and.b32 sb, sb, -8;\n"
        "mbarrier.test_wait.parity.shared::cta.b64 pw, [sb+" STR(SM_EMPTY) "-8*" STR(NX) "], 0;\n"
        TROW(0, z0, z1) TROW(1, z2, z3) TROW(2, z4, z5) TROW(3, z6, z7) TCLK TDL
        "sub.u32 c, c, dl;\n setp.lt.and.u32 pw, sb, %3, pw;\n setp.ge.and.s32 pw, c, 0, pw;\n"
        "add.u32 xs, xs, 8192;\n setp.eq.u32 pk, xs, " STR(SM_R) "-" STR(SM_X) ";\n selp.b32 xs, 0, xs, pk;\n"
        "@pw bra.uni TR;\n"
        "TW:\n setp.ge.u32 pk, sb, %3;\n @pk bra.uni TEND;\n mov.u32 n, 0;\n"
        "TV:\n mbarrier.try_wait.parity.shared::cta.b64 pk, [sb+" STR(SM_EMPTY) "-8*" STR(NX) "], 0;\n"
        "add.u32 n, n, 1;\n setp.lt.and.u32 pk, n, 400000, !pk;\n @pk bra.uni TV;\n"
        "TS:\n" TCLK "sub.u32 c, c, dl;\n setp.lt.s32 pk, c, 0;\n @pk bra.uni TS;\n bra.uni TR;\n"
        "TEND:\n}\n"
        : "+r"(late)
        : "l"(tm), "r"(((NX - nst % NX) % NX) * 16384), "r"(nst * 8), "r"(T0), "r"(p.rate)
#ifdef DBG_TR
          , "l"(g_trace + blockIdx.x * 720)
#endif
        : "memory");
    return late;
}

__device__ __forceinline__ void slow_path(const Params& p) {
    const int lane = threadIdx.x & 31, warp = threadIdx.x >> 5;
#pragma unroll 1
    for (int nl = warp; nl < NPC; nl += 16) {
        const int node = blockIdx.x * NPC + nl;
        float acc[4][8];
#pragma unroll
        for (int w = 0; w < 4; w++)
#pragma unroll
            for (int j = 0; j < 8; j++) acc[w][j] = 0.f;
        if (node < p.N) {
#pragma unroll 1
            for (int e0 = 0; e0 < p.E; e0 += 32) {
                int e = e0 + lane;
                unsigned m = __ballot_sync(~0u, e < p.E && p.dst[e] == node);
                while (m) {
                    int ee = e0 + __ffs(m) - 1; m &= m - 1;
                    int s = p.src[ee];
                    float rw[8];
#pragma unroll
                    for (int j = 0; j < 8; j++) rw[j] = 0.f;
#pragma unroll 1
                    for (int k = 0; k < 16; k++) {
                        float a = __bfloat162float(p.ea[(size_t)ee * 16 + k]);
#pragma unroll
                        for (int j = 0; j < 8; j++) rw[j] += a * __bfloat162float(p.wr[k * 256 + lane * 8 + j]);
                    }
#pragma unroll 1
                    for (int u = 0; u < 4; u++) {
                        float y[8];
#pragma unroll
                        for (int j = 0; j < 8; j++) y[j] = rw[j] * __bfloat162float(p.x[((size_t)s * 4 + u) * 256 + lane * 8 + j]);
#pragma unroll
                        for (int w = 0; w < 4; w++) {
                            float a = 0.f;
#pragma unroll
                            for (int v = 0; v < 4; v++) a += __bfloat162float(p.cg[u * 16 + v * 4 + w]) * __bfloat162float(p.sh[(size_t)ee * 4 + v]);
#pragma unroll
                            for (int j = 0; j < 8; j++) acc[w][j] += a * y[j];
                        }
                    }
                }
            }
        }
#pragma unroll
        for (int w = 0; w < 4; w++) {
            int R = nl * 4 + w;
            sts128(SM_H + (lane >> 3) * HPANEL + R * 128 + (((lane & 7) ^ (R & 7)) << 4),
                   pack2(acc[w][0], acc[w][1]), pack2(acc[w][2], acc[w][3]), pack2(acc[w][4], acc[w][5]), pack2(acc[w][6], acc[w][7]));
        }
    }
}

template <int NN>
__device__ __forceinline__ void out_chunk(float* d, unsigned stg, const CUtensorMap* tmo, int wg, int row0, bool first, unsigned a, bool lead) {
    if (first) asm volatile("bar.sync %0, 128;" ::"r"(wg + 1) : "memory");
#pragma unroll
    for (int n = 0; n < NN / 8; n += 2)
        stsm4t(a + n * 1024, pack2(d[4 * n], d[4 * n + 1]), pack2(d[4 * n + 2], d[4 * n + 3]), pack2(d[4 * n + 4], d[4 * n + 5]), pack2(d[4 * n + 6], d[4 * n + 7]));
    fence_async();
    if (NN == 64) asm volatile("cp.async.bulk.wait_group.read 0;" ::: "memory");
    asm volatile("bar.sync %0, 128;" ::"r"(wg + 1) : "memory");
    if (lead) {
        tma_st(tmo, stg, wg * 64, row0);
        asm volatile("cp.async.bulk.commit_group;" ::: "memory");
    }
}

__global__ void __launch_bounds__(512, 1)
mace_kernel(const __grid_constant__ Params p, const __grid_constant__ CUtensorMap tmx, const __grid_constant__ CUtensorMap tmw,
            const __grid_constant__ CUtensorMap tmo) {
    extern __shared__ __align__(1024) char smem_raw[];
    const unsigned tstart = clk();
    const int tid = threadIdx.x, cta = blockIdx.x;
    const int e0 = cta * EPC + tid * 4;
    const bool has = tid < EPC / 4 && e0 < p.Ef;
    uint4 s4, d4;
    asm volatile("{.reg .pred q; setp.ne.u32 q, %10, 0;\n @q ld.global.nc.v4.u32 {%0,%1,%2,%3}, [%8];\n @q ld.global.nc.v4.u32 {%4,%5,%6,%7}, [%9];}"
        : "=r"(d4.x), "=r"(d4.y), "=r"(d4.z), "=r"(d4.w), "=r"(s4.x), "=r"(s4.y), "=r"(s4.z), "=r"(s4.w) : "l"(p.dst + e0), "l"(p.src + e0), "r"((int)has) : "memory");
    const int lane = tid & 31, warp = __shfl_sync(~0u, tid >> 5, 0);
    const unsigned wbar = SM_MISC, totA = SM_MISC + 80;
    bool slow = p.Ef == 0;
    int total = 0, nst = 0;
    unsigned T0 = 0, cg0 = 0, cg1 = 0, dsc[4];
    if (slow) {
        if (tid < 8) bar_init(wbar + tid * 8, 1);
    } else if (warp >= NXT / 32) {
        unsigned* const ctr = (unsigned*)(p.xch + NCTA * NCTA * NCH);
        unsigned epn;
        if (warp == 15) {
            asm volatile("ld.relaxed.gpu.global.u32 %0, [%1];" : "=r"(epn) : "l"(ctr));
        } else {
#pragma unroll
            for (int k = 0; k < 6; k++) {
                const unsigned i = lane + k * 32, c = i < CAPP / 16 + 8 || i >= CAPP / 8 + 8 ? 0xFFFFFu : 0xFFFF8u;
                sts128(i < CAPP / 8 + 8 ? SM_FULL + i * 16 : wbar + (i - CAPP / 8 - 8) * 16, c << 1, c << 11, c << 1, c << 11);
            }
            fence_async();
            __syncwarp();
            if (lane < 16) asm volatile("mbarrier.arrive.shared::cta.b64 _, [%0];" ::"r"(SM_EMPTY + (lane - 16) * 8) : "memory");
        }
        uint4 w4[8];
        unsigned c4[4];
#pragma unroll
        for (int k = 0; k < 8; k++) asm volatile("ld.global.nc.v4.u32 {%0,%1,%2,%3}, [%4];" : "=r"(w4[k].x), "=r"(w4[k].y), "=r"(w4[k].z), "=r"(w4[k].w) : "l"((const uint4*)p.wr + (tid - NXT + k * 64)));
#pragma unroll
        for (int k = 0; k < 4; k++) asm volatile("ld.global.nc.u16 %0, [%1];" : "=r"(c4[k]) : "l"(p.cg + (lane & 4) * 8 + (lane & 2) * 4 + (lane >> 3) + (k & 1) * 4 + (k & 2) * 8));
        auto put = [&]() {
#pragma unroll
            for (int k = 0; k < 8; k++) sts128(SM_WR + (warp - NXT / 32 + 2 * k) * 528 + lane * 16, w4[k].x, w4[k].y, w4[k].z, w4[k].w);
            asm volatile("prmt.b32 %0, %2, %3, 0x5410;\n prmt.b32 %1, %4, %5, 0x5410;" : "=&r"(cg0), "=r"(cg1) : "r"(c4[0]), "r"(c4[1]), "r"(c4[2]), "r"(c4[3]));
        };
        if (warp == 15) {
            epn = (epn | 255) + 1;
            sts64(totA, epn, 0);
            narrive<7, NXT + 32>();
            nsync<10, NXT + 32>();
            if (lane == 0) asm volatile("red.relaxed.gpu.global.add.u32 [%0], %1;" ::"l"(ctr), "r"(cta ? 1 : 257 - NCTA) : "memory");
            put();
            while (clk() - tstart < POLLT);
            unsigned v; int it = 0;
            do asm volatile("ld.relaxed.gpu.global.u32 %0, [%1];" : "=r"(v) : "l"(ctr) : "memory");
            while (v != epn && ++it < 4096);
            narrive<8, NXT + 32>();
#ifdef DBG_PRO
            sts32(totA + 16, it * 2);
#endif
            nsync<9, NXT + 32>();
            uint4 u[NBW];
#pragma unroll
            for (int q = 0; q < NBW; q++) u[q] = lds128(SM_BKT + (lane * NBW + q) * 16);
            const unsigned mx = lds32(SM_CNT + min(lane, NXT / 32 - 1) * 4), bad = lds32(totA + 4);
            unsigned sum = 0;
#pragma unroll
            for (int q = 0; q < NBW; q++) sum += u[q].x + u[q].y + u[q].z + u[q].w;
            unsigned inc = sum;
#pragma unroll
            for (int o = 1; o < 32; o <<= 1) asm volatile("{.reg .pred q; .reg .b32 t; shfl.sync.up.b32 t|q, %0, %1, 0, -1;\n @q add.u32 %0, %0, t;}" : "+r"(inc) : "r"(o));
            sum = inc - sum;
#pragma unroll
            for (int q = 0; q < NBW; q++) {
                const unsigned a2 = sum + u[q].x + u[q].y;
                sts128(SM_BKT + (lane * NBW + q) * 16, sum, sum + u[q].x, a2, a2 + u[q].z);
                sum = a2 + u[q].z + u[q].w;
            }
            const unsigned t0 = tstart + ((__reduce_max_sync(~0u, mx) & 0xFFF8) << 1) + T0DELTA;
            if (lane == 31) sts64(totA + 8, (inc >> 2) + bad, t0);
        } else {
            if (elect()) {
                asm volatile("prefetch.tensormap [%0];" ::"l"(&tmx) : "memory");
                asm volatile("prefetch.tensormap [%0];" ::"l"(&tmw) : "memory");
                asm volatile("prefetch.tensormap [%0];" ::"l"(&tmo) : "memory");
                if (cta < 128) pf_l2(p.wo + cta * 512, 1024);
            }
            put();
#pragma unroll
            for (int i = 0; i < PFLEAD / 2; i++) {
                if (i == PF1) while (clk() - tstart < PFT);
                if (elect()) pf_l2(p.x + (size_t)min(i * NCTA + cta, p.N / 2 - 1) * 2048, 4096);
            }
        }
        cta_sync();
        total = __shfl_sync(~0u, lds32(totA + 8), 0);
        slow = total > CAP;
        nst = (total + 7) >> 3;
    } else {
        {
            const unsigned du = DUM + (((cta * NCH + tid) & 31) << (18 + BSH));
#pragma unroll
            for (int k = 0; k < 3; k++) sts128(SM_STAGE + (tid + k * NXT) * 16, du, du, du, ~0u);
            if (tid < NCTA) sts32(SM_CNT + tid * 4, 0);
        }
        TK(24, e0);
        nsync<6, NXT>();
        TK(0, e0);
        const bool h2 = tid < NCTA * NCH - 2 * NXT;
        unsigned cc[3];
        const char* xo[3];
#pragma unroll
        for (int k = 0; k < 3; k++) {
            const unsigned i = tid + k * NXT;
            cc[k] = (i * 6554) >> 16;
            xo[k] = pin64((const char*)(p.xch + (cc[k] * ((NCTA - 1) * NCH) + cta * NCH + i)));
        }
        TK(26, d4.x);
        if (has) {
            const unsigned ss[4] = {s4.x, s4.y, s4.z, s4.w}, dd[4] = {d4.x, d4.y, d4.z, d4.w};
            unsigned c[4], o[4];
#pragma unroll
            for (int j = 0; j < 4; j++) { c[j] = __umulhi(dd[j], 0xFFFFFFFFu / NPC + 1); o[j] = atoms_add(SM_CNT + c[j] * 4, 0x15558); }
#pragma unroll
            for (int j = 0; j < 4; j++) {
                const unsigned dl = dd[j] - c[j] * NPC;
                sts32(SM_STAGE + (c[j] * (NCH * 4) + min(o[j] >> 16, NCH * 4 - 1)) * 4, (ss[j] << 18) + (tid * 4 + j) + dl * 2048 + (dl * 43 >> 8) * 4096);
            }
        }
        TK(28, e0);
        nsync<7, NXT + 32>();
        TK(1, e0);
        const unsigned ep = (lds32(totA) << 8) | 0x80000000u;
        {
            const unsigned tag = ep | (min((clk() - tstart) >> 4, 0x1FFFu) << 3);
            uint4 v[3];
#pragma unroll
            for (int k = 0; k < 3; k++) v[k] = lds128(SM_STAGE + (tid + k * NXT) * 16);
#pragma unroll
            for (int k = 0; k < 3; k++)
                if (k < 2 || h2) asm volatile(XST " [%0], {%1,%2,%3,%4};" ::"l"(xo[k]), "r"(v[k].x), "r"(v[k].y), "r"(v[k].z), "r"(tag + (v[k].w != ~0u)) : "memory");
        }
        narrive<10, NXT + 32>();
        TK(16, e0);
        if ((unsigned)__cvta_generic_to_shared(smem_raw) != SB) __trap();
        if (tid < NBW * 32 + 8) { const unsigned v = tid < NBW * 32 ? 0 : CAP * 4; sts128(SM_BKT + tid * 16, v, v, v, v); }
        if (tid < 384) { const unsigned v = tid < 381 ? (p.N - 1) << 18 : 0; sts128(SM_EID + tid * 16, v, v, v, v); }
        if (tid < 1392 / 4) sts128(SM_SRC + tid * 16, NCONS << 14, NCONS << 14, NCONS << 14, NCONS << 14);
        if (tid < 159) sts128(SM_BITS + tid * 16, 0, 0, 0, 0);
#pragma unroll
        for (int k = 0; k < 4; k++) {
            const unsigned pos = tid + k * (NCONS * 32), st = pos >> 3, j = pos & 7;
            dsc[k] = pin(pos | (((st % NX) * 8 + j) << 11) | ((((st % NR) * 8 + j) * (RSTR / 32)) << 21));
        }
        const char* const xi = pin64((const char*)(p.xch + cta * (NCTA * NCH) + tid));
        uint4 rc[3];
        rc[0].w = rc[1].w = 0;
        rc[2].w = h2 ? 0 : ep;
        rc[2].x = ~0u;
        nsync<8, NXT + 32>();
        TK(18, e0);
        {
            bool bad;
            int it = 0;
            do {
#pragma unroll
                for (int k = 0; k < 3; k++)
                    asm volatile("{.reg .pred q; .reg .b32 t; xor.b32 t, %3, %5; setp.gt.u32 q, t, 0xFFFF;\n @q ld.relaxed.gpu.global.v4.u32 {%0,%1,%2,%3}, [%4];}"
                                 : "+r"(rc[k].x), "+r"(rc[k].y), "+r"(rc[k].z), "+r"(rc[k].w) : "l"(xi + k * (NXT * 16)), "r"(ep) : "memory");
                bad = ((rc[0].w ^ ep) | (rc[1].w ^ ep) | (rc[2].w ^ ep)) > 0xFFFF;
            } while (__any_sync(~0u, bad) && ++it < 4096);
            if (bad || ((rc[0].w | rc[1].w | rc[2].w) & 1)) {
                rc[0].x = rc[1].x = rc[2].x = ~0u;
                sts32(totA + 4, CAP + 1);
            }
#ifdef DBG_PRO
            if (tid == 0) sts32(totA + 20, it * 2);
#endif
        }
        TK(2, e0);
        unsigned ord[3][3], ba[3][3], ve[3][3];
#pragma unroll
        for (int k = 0; k < 3; k++) {
            const unsigned rr[3] = {rc[k].x, rc[k].y, rc[k].z};
            if (rr[0] < DUM) {
#pragma unroll
                for (int j = 0; j < 3; j++) { ba[k][j] = pin((rr[j] >> (18 + BSH)) * 4); ord[k][j] = atoms_add(SM_BKT + ba[k][j], 4); }
            }
        }
        sts32(SM_CNT + warp * 4, __reduce_max_sync(~0u, max(rc[0].w, max(rc[1].w, rc[2].w))));
        narrive<9, NXT + 32>();
        TK(15, e0);
#pragma unroll
        for (int k = 0; k < 3; k++) {
            const unsigned rr[3] = {rc[k].x, rc[k].y, rc[k].z};
#pragma unroll
            for (int j = 0; j < 3; j++) ve[k][j] = pin((rr[j] & 0xFFFC07FF) + cc[k] * EPC);
        }
        cta_sync();
        TK(19, e0);
        total = __shfl_sync(~0u, lds32(totA + 8), 0);
        T0 = lds32(totA + 12);
#pragma unroll
        for (int k = 0; k < 3; k++) {
            if (rc[k].x < DUM) {
#pragma unroll
                for (int j = 0; j < 3; j++) ord[k][j] += lds32(SM_BKT + ba[k][j]);
#pragma unroll
                for (int j = 0; j < 3; j++)
                    asm volatile("{.reg .pred q; setp.lt.u32 q, %0, " STR(CAP) "*4;\n @q st.shared.u32 [%0+" STR(SM_EID) "], %1;}" ::"r"(ord[k][j]), "r"(ve[k][j]) : "memory");
            }
        }
        slow = total > CAP;
        if (!slow) {
            if (warp < NCONS) narrive<0, 512>();
#pragma unroll
            for (int k = 0; k < 3; k++) {
                const unsigned rr[3] = {rc[k].x, rc[k].y, rc[k].z};
                if (rr[0] < DUM) {
#pragma unroll
                    for (int j = 0; j < 3; j++)
                        asm volatile("{.reg .pred q; setp.lt.u32 q, %0, " STR(CAP) "*4;\n @q st.shared.u32 [%0+" STR(SM_SRC) "], %1;}" ::"r"(ord[k][j]), "r"(rr[j]) : "memory");
                }
            }
            if (warp == NCONS) narrive<11, NXT>();
        }
        nst = (total + 7) >> 3;
        const unsigned lim = (nst % NX) << 14;
#pragma unroll
        for (int k = 0; k < 4; k++) dsc[k] = pin(dsc[k] - lim + ((dsc[k] & 0x3C000) >= lim ? 0 : NX << 14));
        TK(20, e0);
#ifdef DBG_PRO
        if (tid == 0) { sts128(SM_NEXT + CAPP * 4, tk0, tk1, tk24, tk26); sts128(SM_NEXT + CAPP * 4 + 16, tk28, tk16, tk2, tk15); sts128(SM_NEXT + CAPP * 4 + 32, tk19, tk20, tk18, tstart); }
#endif
    }

    int wid = warp;
    if (slow) {
        asm volatile("fence.mbarrier_init.release.cluster;" ::: "memory");
        fence_async();
        cta_sync();
        if (tid < 4) { bar_expect(wbar + tid * 8, 16384); tma_2d(SB + tid * 16384, &tmw, wbar + tid * 8, tid * 64, 0); }
        slow_path(p);
    } else if (warp < NCONS) {
        nsync<11, NXT>();
        TK(3, tid);
        unsigned q[4], a[4];
        const bool k3 = warp * 32 + 3 * NCONS * 32 < total;
#pragma unroll
        for (int k = 0; k < 4; k++) if (k < 3 || k3) q[k] = lds32(SM_SRC + tid * 4 + k * (NCONS * 128));
#pragma unroll
        for (int k = 0; k < 4; k++) if (k < 3 || k3) {
            a[k] = ((q[k] >> 14) & 15) * (BW * 4) + warp * 4;
            asm volatile("red.shared.or.b32 [%0], %1;" ::"r"(SM_BITS + k * (NCONS * 4) + a[k]), "r"(1u << lane) : "memory");
        }
        __syncwarp();
#pragma unroll
        for (int k = 0; k < 4; k++) if (k < 3 || k3) a[k] = lds32(SM_BITS + k * (NCONS * 4) + a[k]);
#pragma unroll
        for (int k = 0; k < 4; k++) if (k < 3 || k3)
            sts32(SM_NEXT + k * (NCONS * 128) + ((warp * 32) | ((lane + 31 - __clz(__funnelshift_r(a[k], a[k], lane))) & 31)) * 4, dsc[k] | ((q[k] << 7) & 0x1C0000));
        asm volatile("bar.sync 5, %0;" ::"n"(NCONS * 32) : "memory");
        TK(21, tid);
        unsigned head;
        {
            const unsigned c = 31 - lane, m0 = lds32(SM_BITS + warp * (BW * 4) + c * 4), m1 = lds32(SM_BITS + warp * (BW * 4) + 128 + min(c, 12) * 4);
            const unsigned l0 = m0 ? c * 32 + 31 - __clz(m0) : CAPP - 1, l1 = m1 ? c * 32 + 1055 - __clz(m1) : CAPP - 1;
            const unsigned f0 = lds32(SM_NEXT + l0 * 4), f1 = lane ? lds32(SM_NEXT + l1 * 4) : 0x1C0000 | (warp << 21);
            const unsigned b0 = __ballot_sync(~0u, m0), b1 = __ballot_sync(~0u, m1) | 1, lt = (1u << lane) - 1;
            const unsigned h1 = __shfl_sync(~0u, f1, 31 - __clz(b1)), n1 = __shfl_sync(~0u, f1, 31 - __clz(b1 & lt));
            const unsigned h0 = __shfl_sync(~0u, f0, 31 - __clz(b0)), n0 = __shfl_sync(~0u, f0, 31 - __clz(b0 & lt));
            sts32(SM_NEXT + l0 * 4, b0 & lt ? n0 : h1);
            sts32(SM_NEXT + l1 * 4, n1);
            head = b0 ? h0 : h1;
            __syncwarp();
        }
        TK(22, tid);
#ifdef DBG_PRO
        if (tid == 0) sts128(SM_NEXT + CAPP * 4 + 48, tk3, tk21, tk22, 0);
#endif
        wid = consumer(head);
    } else if (warp == NCONS) {
        cta_sync();
        STAMPS(636 + 26, clk() | 1);
        const unsigned late = issuer(&tmx, p, nst, T0);
        wid = NCONS;
        if ((total & 7) && elect()) asm volatile("mbarrier.arrive.shared::cta.b64 _, [%0], %1;" ::"r"(SM_EMPTY + nst * 8 - 8), "r"(8 - (total & 7)) : "memory");
        STAMPS(11, clk() | 1); STAMPS(14, lds32(SM_MISC + 104)); STAMPS(12, tstart & ~1);
#pragma unroll 1
        for (int i = 0; i < 4; i++) {
            bwait(SM_EMPTY + (nst + i - NX) * 8);
            if (elect()) { bar_expect(wbar + i * 8, 16384); tma_2d(SB + i * 16384, &tmw, wbar + i * 8, i * 64, 0); }
        }
#ifdef DBG_TR
        for (int i = lane; i < nst; i += 32) g_trace[(cta * 180 + i) * 4 + 3] = lds32(SM_TR + i * 8) - T0;
#endif
#ifdef DBG_PRO
        if (lane < 15) { const unsigned ix[15] = {0, 1, 24, 26, 28, 16, 2, 15, 19, 20, 18, 31, 3, 21, 22}; unsigned j = 0;
#pragma unroll
            for (int q = 0; q < 15; q++) j = lane == q ? ix[q] : j;
            const unsigned v = lds32(SM_NEXT + CAPP * 4 + lane * 4); g_times[cta * 32 + j] = j == 31 ? v & ~1 : v | 1; }
        STAMPW(13, lds32(totA + 16)); STAMPW(17, lds32(totA + 20));
#endif
#ifdef DBG_H
        STAMPS(8, late & ~1);
#endif
        STAMPS(10, clk() | 1); STAMPS(7, T0 | 1);
    } else {
        const unsigned ewait = recorder(p, __shfl_sync(~0u, (tid >> 5) & 1, 0), nst, cg0, cg1);
        wid = NCONS + 1 + ((ewait >> 3) & 1);
#ifdef DBG_R
        if (wid == 15) STAMPW(12, ewait); else STAMPW(11, ewait);
#endif
    }

    wid = __shfl_sync(~0u, wid, 0);
    const int wg = wid >> 2, wq = wid & 3;
    int ln;
    asm volatile("mov.u32 %0, %%laneid;" : "=r"(ln));
    const bool lead = (LWG < 4 ? wg == LWG : wq == 0) && ln == 0;
    const int wl = LWG < 4 ? wq : wg;
    unsigned af[16][4];
    const unsigned wt = SB + wg * 16384;
    const unsigned wa = wt + (((ln >> 4) * 8 + (ln & 7)) << 7) + (((2 * wq + ((ln >> 3) & 1)) ^ (ln & 7)) << 4);
    STAMPL(13);
    bwait(wbar + wg * 8);
#pragma unroll
    for (int k = 0; k < 8; k++) ldsm4t(af[k], wa + k * 2048);
    fence_async();
    cta_sync();
    STAMPL(5);
    if (lead) { bar_expect(wbar + 32 + wl * 8, 16384); tma_2d(SB + wl * 16384, &tmw, wbar + 32 + wl * 8, wl * 64, 128); }
    const uint64_t desc0 = (uint64_t)(((SM_H) >> 4) & 0x3FFF) | (1ull << 16) | (64ull << 32) | (1ull << 62);
    float d[32];
    const int row0 = cta * (NPC * 4) + wq * 16;
    const unsigned ws = wt + wq * 2048;
    wg_fence();
#pragma unroll
    for (int k = 0; k < 8; k++) wgmma_rs<64>(d, af[k], desc0 + (k >> 2) * (HPANEL >> 4) + (k & 3) * 2, k != 0);
    wg_commit();
    bwait(wbar + 32 + wg * 8);
#pragma unroll
    for (int k = 0; k < 8; k++) ldsm4t(af[8 + k], wa + k * 2048);
    wg_fence();
#pragma unroll
    for (int k = 8; k < 16; k++) wgmma_rs<64>(d, af[k], desc0 + (k >> 2) * (HPANEL >> 4) + (k & 3) * 2, 1);
    wg_commit();
    wg_wait0();
    out_chunk<64>(d, ws, &tmo, wg, row0, true, wa, ln == 0);
#pragma unroll 1
    for (int c = 1; c < 4; c++) {
        wg_fence();
#pragma unroll
        for (int k = 0; k < 16; k++) wgmma_rs<64>(d, af[k], desc0 + c * 512 + (k >> 2) * (HPANEL >> 4) + (k & 3) * 2, k != 0);
        wg_commit();
        wg_wait0();
        out_chunk<64>(d, ws + (c & 1) * 8192, &tmo, wg, row0 + c * 64, false, wa + (c & 1) * 8192, ln == 0);
    }
    wg_fence();
#pragma unroll
    for (int k = 0; k < 16; k++) wgmma_rs<48>(d, af[k], desc0 + 4 * 512 + (k >> 2) * (HPANEL >> 4) + (k & 3) * 2, k != 0);
    wg_commit();
    wg_wait0();
    out_chunk<48>(d, ws, &tmo, wg, row0 + 256, false, wa, ln == 0 && wq < 3);
    asm volatile("cp.async.bulk.wait_group.read 0;" ::: "memory");
    STAMPL(6);
#ifdef DBG_TIMES
    cta_sync();
    if (wid == 8) STAMPS(4, clk() | 1);
    cta_sync();
    if (wid == 0 && ln >= 4 && ln < 21) g_times[cta * 32 + (ln == 12 ? 31 : ln)] = lds32(SM_BITS + ln * 4);
#endif
#ifdef DBG_GT
    { unsigned g; asm volatile("mov.u32 %0, %%globaltimer_lo;" : "=r"(g)); STAMPW(30, g & ~1); }
#endif
}

typedef CUresult (*EncFn)(CUtensorMap*, CUtensorMapDataType, cuuint32_t, void*, const cuuint64_t*, const cuuint64_t*, const cuuint32_t*,
                          const cuuint32_t*, CUtensorMapInterleave, CUtensorMapSwizzle, CUtensorMapL2promotion, CUtensorMapFloatOOBfill);

extern "C" void kernel_launch(void* const* d_in, const int* in_sizes, int n_in, void* d_out, int out_size) {
    static EncFn enc = nullptr;
    static int nsm = 0;
    static void* xch = nullptr;
    if (!enc) {
        void* fn = nullptr; cudaDriverEntryPointQueryResult qr;
        cudaGetDriverEntryPoint("cuTensorMapEncodeTiled", &fn, cudaEnableDefault, &qr);
        enc = (EncFn)fn;
        cudaGetSymbolAddress(&xch, g_xch);
        int dev = 0; cudaGetDevice(&dev);
        cudaDeviceGetAttribute(&nsm, cudaDevAttrMultiProcessorCount, dev);
        cudaFuncSetAttribute(mace_kernel, cudaFuncAttributeMaxDynamicSharedMemorySize, SM_TOTAL);
    }
    Params p;
    p.x = (const __nv_bfloat16*)d_in[0]; p.src = (const int*)d_in[1]; p.dst = (const int*)d_in[2];
    p.sh = (const __nv_bfloat16*)d_in[3]; p.ea = (const __nv_bfloat16*)d_in[4]; p.cg = (const __nv_bfloat16*)d_in[5];
    p.wr = (const __nv_bfloat16*)d_in[6]; p.wo = (const __nv_bfloat16*)d_in[7];
    p.N = in_sizes[0] / 1024; p.E = in_sizes[1];
    p.Ef = (nsm >= NCTA && p.N <= NCTA * NPC && p.E <= NCTA * EPC && p.N > 1 && (p.E & 3) == 0) ? p.E : 0;
    p.xch = (uint4*)xch;
    p.rate = (unsigned)((double)PACE * ((double)p.E / 160000.0) * 16384.0 / (double)p.N);
    p.zero = 0;
    CUtensorMap tmx, tmw, tmo;
    const cuuint32_t es[3] = {1, 1, 1};
    {
        cuuint64_t dims[3] = {64, (cuuint64_t)p.N * 4, 4}; cuuint64_t str[2] = {512, 128}; cuuint32_t box[3] = {64, 4, 4};
        enc(&tmx, CU_TENSOR_MAP_DATA_TYPE_BFLOAT16, 3, d_in[0], dims, str, box, es, CU_TENSOR_MAP_INTERLEAVE_NONE, CU_TENSOR_MAP_SWIZZLE_128B, CU_TENSOR_MAP_L2_PROMOTION_NONE, CU_TENSOR_MAP_FLOAT_OOB_FILL_NONE);
    }
    {
        cuuint64_t dims[2] = {256, 256}; cuuint64_t str[1] = {512}; cuuint32_t box[2] = {64, 128};
        enc(&tmw, CU_TENSOR_MAP_DATA_TYPE_BFLOAT16, 2, d_in[7], dims, str, box, es, CU_TENSOR_MAP_INTERLEAVE_NONE, CU_TENSOR_MAP_SWIZZLE_128B, CU_TENSOR_MAP_L2_PROMOTION_NONE, CU_TENSOR_MAP_FLOAT_OOB_FILL_NONE);
    }
    {
        cuuint64_t dims[2] = {256, (cuuint64_t)p.N * 4}; cuuint64_t str[1] = {512}; cuuint32_t box[2] = {64, 16};
        enc(&tmo, CU_TENSOR_MAP_DATA_TYPE_BFLOAT16, 2, d_out, dims, str, box, es, CU_TENSOR_MAP_INTERLEAVE_NONE, CU_TENSOR_MAP_SWIZZLE_128B, CU_TENSOR_MAP_L2_PROMOTION_NONE, CU_TENSOR_MAP_FLOAT_OOB_FILL_NONE);
    }
    const int grid = p.Ef ? NCTA : (p.N + NPC - 1) / NPC;
    mace_kernel<<<grid, 512, SM_TOTAL>>>(p, tmx, tmw, tmo);
}
```
